```python
import torch

def _softmax(x, axis=-1):
    return torch.softmax(x, dim=axis)
def _gelu(x):
    return torch.nn.functional.gelu(x, approximate="tanh")
def _silu(x):
    return torch.nn.functional.silu(x)
def _sigmoid(x):
    return torch.sigmoid(x)
def _layernorm(x, axis=-1, eps=1e-5):
    m = x.mean(dim=axis, keepdim=True)
    v = x.var(dim=axis, keepdim=True, unbiased=False)
    return (x - m) / torch.sqrt(v + eps)
def _scatter_add(tgt, idx, src, axis=0):
    return tgt.clone().index_add_(axis, idx, src)
def _segment_sum(src, seg, n):
    out = torch.zeros((n,) + src.shape[1:], dtype=src.dtype)
    return out.index_add_(0, seg, src)
def _pad(x, pw):
    flat = tuple(v for pair in reversed(pw) for v in pair)
    return torch.nn.functional.pad(x, flat)

kernel_name = 'gated_mix__linear_kernel_hedgehog__ssm_conv_s4d__prompt'

def setup_inputs():

    _w = (lambda a: (lambda t: t.to(torch.bfloat16) if t.is_floating_point() else t)(torch.as_tensor(a)))
    def _A_setup():
        B, S, D, H = 1, 2048, 640, 32
        Dh = D // H
        return {
            "x": _w((lambda *s: torch.randn(*s, dtype=torch.bfloat16) * 0.05)(B, S, D)),
            "wqkv": _w((lambda *s: torch.randn(*s, dtype=torch.bfloat16) * 0.8)(D, 3 * D)),
            "w_phi": _w((lambda *s: torch.randn(*s, dtype=torch.bfloat16) * 0.8)(H, Dh, Dh) * (Dh ** -0.5)),
            "wo": _w((lambda *s: torch.randn(*s, dtype=torch.bfloat16) * 0.05)(D, D)),
        }
    _A_in = _A_setup()

    def _B_setup():
        Bsz, L, D, N = 1, 2048, 640, 128
        return {
            "u": _w((lambda *s: torch.randn(*s, dtype=torch.bfloat16) * 0.05)(Bsz, L, D)),
            "log_A_real": _w((lambda *s: torch.randn(*s, dtype=torch.bfloat16) * 6.4)(D, N) * 0.5),
            "A_imag": _w((lambda *s: torch.randn(*s, dtype=torch.bfloat16) * 0.05)(D, N) * 3.14),
            "C_real": _w((lambda *s: torch.randn(*s, dtype=torch.bfloat16) * 0.2)(D, N) / N ** 0.5),
            "C_imag": _w((lambda *s: torch.randn(*s, dtype=torch.bfloat16) * 0.2)(D, N) / N ** 0.5),
            "log_dt": _w((lambda *s: torch.randn(*s, dtype=torch.bfloat16) * 0.05)(D) * 0.5 - 4.0),
            "D_skip": _w((lambda *s: torch.randn(*s, dtype=torch.bfloat16) * 0.05)(D)),
        }
    _B_in = _B_setup()

    return {
        "A_x": _A_in["x"],
        "A_wqkv": _A_in["wqkv"],
        "A_w_phi": _A_in["w_phi"],
        "A_wo": _A_in["wo"],
        "B_u": _B_in["u"],
        "B_log_A_real": _B_in["log_A_real"],
        "B_A_imag": _B_in["A_imag"],
        "B_C_real": _B_in["C_real"],
        "B_C_imag": _B_in["C_imag"],
        "B_log_dt": _B_in["log_dt"],
        "B_D_skip": _B_in["D_skip"],
        "gate_w": _w((lambda *s: torch.randn(*s, dtype=torch.bfloat16) * 0.05)(640) * 16.0),
    }

def reference(A_x, A_wqkv, A_w_phi, A_wo, B_u, B_log_A_real, B_A_imag, B_C_real, B_C_imag, B_log_dt, B_D_skip, gate_w):
    def _A_ref(x, wqkv, w_phi, wo):
        B, S, D = x.shape
        H = 32; Dh = D // H
        qkv = (lambda x, *d: x.permute(*d))((x @ wqkv).reshape(B, S, 3, H, Dh), 2, 0, 3, 1, 4)
        q, k, v = qkv[0], qkv[1], qkv[2]
        pq = torch.einsum("bhsd,hdf->bhsf", q, w_phi)
        pk = torch.einsum("bhsd,hdf->bhsf", k, w_phi)
        phi_q = torch.concatenate([_softmax(pq, axis=-1), _softmax(-pq, axis=-1)], axis=-1)
        phi_k = torch.concatenate([_softmax(pk, axis=-1), _softmax(-pk, axis=-1)], axis=-1)
        kv = torch.einsum("bhsf,bhsd->bhfd", phi_k, v)
        z  = torch.einsum("bhsf->bhf", phi_k)
        num = torch.einsum("bhqf,bhfd->bhqd", phi_q, kv)
        den = torch.einsum("bhqf,bhf->bhq", phi_q, z)[..., None] + 1e-6
        o = num / den
        return (lambda x, *d: x.permute(*d))(o, 0, 2, 1, 3).reshape(B, S, D) @ wo

    def _B_ref(u, log_A_real, A_imag, C_real, C_imag, log_dt, D_skip):
        L = u.shape[1]
        dt = torch.exp(log_dt)
        A = -torch.exp(log_A_real) + 1j * A_imag
        C = (C_real + 1j * C_imag) * dt[:, None]
        pos = (lambda x, dt: x.to(dt))(torch.arange(L), log_dt.dtype)
        P = torch.exp((A * dt[:, None])[:, :, None] * pos[None, None, :])
        K = 2.0 * torch.einsum("dn,dnl->dl", C, P).real
        L2 = 2 * L
        u_t = (lambda x, *d: x.permute(*d))(u, 0, 2, 1)
        Kf = (lambda x, *a, **k: torch.fft.rfft(x.float(), *a, **k))(K, L2)
        Uf = (lambda x, *a, **k: torch.fft.rfft(x.float(), *a, **k))(u_t, L2)
        y = (lambda x, *a, **k: torch.fft.irfft(x, *a, **k).to(torch.bfloat16))(Uf * Kf[None, :, :], L2)[:, :, :L]
        y = (lambda x, *d: x.permute(*d))(y, 0, 2, 1)
        return y + u * D_skip[None, None, :]

    x = A_x
    g = _sigmoid((x * gate_w).sum(-1, keepdims=True))
    a = _A_ref(x, A_wqkv, A_w_phi, A_wo)
    b = _B_ref(x, B_log_A_real, B_A_imag, B_C_real, B_C_imag, B_log_dt, B_D_skip)
    return g * a + (1 - g) * b
```

```cpp
#include <cuda_runtime.h>
#include <cuda.h>
#include <cuda_bf16.h>
#include <stdint.h>

namespace {

template<int N> struct WG;
template<> struct WG<8> {
  template<int TB> static __device__ __forceinline__ void rs(float* d, uint32_t a0, uint32_t a1, uint32_t a2, uint32_t a3, uint64_t b, int sc) {
    asm volatile("{.reg .pred p; setp.ne.b32 p, %9, 0; wgmma.mma_async.sync.aligned.m64n8k16.f32.bf16.bf16 {%0,%1,%2,%3},{%4,%5,%6,%7},%8,p,1,1,%10;}"
      : "+f"(d[0]),"+f"(d[1]),"+f"(d[2]),"+f"(d[3]) : "r"(a0),"r"(a1),"r"(a2),"r"(a3),"l"(b),"r"(sc),"n"(TB));
  }
};
template<> struct WG<16> {
  template<int TB> static __device__ __forceinline__ void rs(float* d, uint32_t a0, uint32_t a1, uint32_t a2, uint32_t a3, uint64_t b, int sc) {
    asm volatile("{.reg .pred p; setp.ne.b32 p, %13, 0; wgmma.mma_async.sync.aligned.m64n16k16.f32.bf16.bf16 {%0,%1,%2,%3,%4,%5,%6,%7},{%8,%9,%10,%11},%12,p,1,1,%14;}"
      : "+f"(d[0]),"+f"(d[1]),"+f"(d[2]),"+f"(d[3]),"+f"(d[4]),"+f"(d[5]),"+f"(d[6]),"+f"(d[7]) : "r"(a0),"r"(a1),"r"(a2),"r"(a3),"l"(b),"r"(sc),"n"(TB));
  }
};
template<> struct WG<24> {
  template<int TB> static __device__ __forceinline__ void rs(float* d, uint32_t a0, uint32_t a1, uint32_t a2, uint32_t a3, uint64_t b, int sc) {
    asm volatile("{.reg .pred p; setp.ne.b32 p, %17, 0; wgmma.mma_async.sync.aligned.m64n24k16.f32.bf16.bf16 {%0,%1,%2,%3,%4,%5,%6,%7,%8,%9,%10,%11},{%12,%13,%14,%15},%16,p,1,1,%18;}"
      : "+f"(d[0]),"+f"(d[1]),"+f"(d[2]),"+f"(d[3]),"+f"(d[4]),"+f"(d[5]),"+f"(d[6]),"+f"(d[7]),"+f"(d[8]),"+f"(d[9]),"+f"(d[10]),"+f"(d[11]) : "r"(a0),"r"(a1),"r"(a2),"r"(a3),"l"(b),"r"(sc),"n"(TB));
  }
};
template<> struct WG<32> {
  template<int TB> static __device__ __forceinline__ void rs(float* d, uint32_t a0, uint32_t a1, uint32_t a2, uint32_t a3, uint64_t b, int sc) {
    asm volatile("{.reg .pred p; setp.ne.b32 p, %21, 0; wgmma.mma_async.sync.aligned.m64n32k16.f32.bf16.bf16 {%0,%1,%2,%3,%4,%5,%6,%7,%8,%9,%10,%11,%12,%13,%14,%15},{%16,%17,%18,%19},%20,p,1,1,%22;}"
      : "+f"(d[0]),"+f"(d[1]),"+f"(d[2]),"+f"(d[3]),"+f"(d[4]),"+f"(d[5]),"+f"(d[6]),"+f"(d[7]),"+f"(d[8]),"+f"(d[9]),"+f"(d[10]),"+f"(d[11]),"+f"(d[12]),"+f"(d[13]),"+f"(d[14]),"+f"(d[15]) : "r"(a0),"r"(a1),"r"(a2),"r"(a3),"l"(b),"r"(sc),"n"(TB));
  }
};
template<> struct WG<40> {
  template<int TA,int TB> static __device__ __forceinline__ void ss(float* d, uint64_t a, uint64_t b, int sc) {
    asm volatile("{.reg .pred p; setp.ne.b32 p, %22, 0; wgmma.mma_async.sync.aligned.m64n40k16.f32.bf16.bf16 {%0,%1,%2,%3,%4,%5,%6,%7,%8,%9,%10,%11,%12,%13,%14,%15,%16,%17,%18,%19},%20,%21,p,1,1,%23,%24;}"
      : "+f"(d[0]),"+f"(d[1]),"+f"(d[2]),"+f"(d[3]),"+f"(d[4]),"+f"(d[5]),"+f"(d[6]),"+f"(d[7]),"+f"(d[8]),"+f"(d[9]),"+f"(d[10]),"+f"(d[11]),"+f"(d[12]),"+f"(d[13]),"+f"(d[14]),"+f"(d[15]),"+f"(d[16]),"+f"(d[17]),"+f"(d[18]),"+f"(d[19]) : "l"(a),"l"(b),"r"(sc),"n"(TA),"n"(TB));
  }
  template<int TB> static __device__ __forceinline__ void rs(float* d, uint32_t a0, uint32_t a1, uint32_t a2, uint32_t a3, uint64_t b, int sc) {
    asm volatile("{.reg .pred p; setp.ne.b32 p, %25, 0; wgmma.mma_async.sync.aligned.m64n40k16.f32.bf16.bf16 {%0,%1,%2,%3,%4,%5,%6,%7,%8,%9,%10,%11,%12,%13,%14,%15,%16,%17,%18,%19},{%20,%21,%22,%23},%24,p,1,1,%26;}"
      : "+f"(d[0]),"+f"(d[1]),"+f"(d[2]),"+f"(d[3]),"+f"(d[4]),"+f"(d[5]),"+f"(d[6]),"+f"(d[7]),"+f"(d[8]),"+f"(d[9]),"+f"(d[10]),"+f"(d[11]),"+f"(d[12]),"+f"(d[13]),"+f"(d[14]),"+f"(d[15]),"+f"(d[16]),"+f"(d[17]),"+f"(d[18]),"+f"(d[19]) : "r"(a0),"r"(a1),"r"(a2),"r"(a3),"l"(b),"r"(sc),"n"(TB));
  }
};
template<> struct WG<48> {
  template<int TA,int TB> static __device__ __forceinline__ void ss(float* d, uint64_t a, uint64_t b, int sc) {
    asm volatile("{.reg .pred p; setp.ne.b32 p, %26, 0; wgmma.mma_async.sync.aligned.m64n48k16.f32.bf16.bf16 {%0,%1,%2,%3,%4,%5,%6,%7,%8,%9,%10,%11,%12,%13,%14,%15,%16,%17,%18,%19,%20,%21,%22,%23},%24,%25,p,1,1,%27,%28;}"
      : "+f"(d[0]),"+f"(d[1]),"+f"(d[2]),"+f"(d[3]),"+f"(d[4]),"+f"(d[5]),"+f"(d[6]),"+f"(d[7]),"+f"(d[8]),"+f"(d[9]),"+f"(d[10]),"+f"(d[11]),"+f"(d[12]),"+f"(d[13]),"+f"(d[14]),"+f"(d[15]),"+f"(d[16]),"+f"(d[17]),"+f"(d[18]),"+f"(d[19]),"+f"(d[20]),"+f"(d[21]),"+f"(d[22]),"+f"(d[23]) : "l"(a),"l"(b),"r"(sc),"n"(TA),"n"(TB));
  }
  template<int TB> static __device__ __forceinline__ void rs(float* d, uint32_t a0, uint32_t a1, uint32_t a2, uint32_t a3, uint64_t b, int sc) {
    asm volatile("{.reg .pred p; setp.ne.b32 p, %29, 0; wgmma.mma_async.sync.aligned.m64n48k16.f32.bf16.bf16 {%0,%1,%2,%3,%4,%5,%6,%7,%8,%9,%10,%11,%12,%13,%14,%15,%16,%17,%18,%19,%20,%21,%22,%23},{%24,%25,%26,%27},%28,p,1,1,%30;}"
      : "+f"(d[0]),"+f"(d[1]),"+f"(d[2]),"+f"(d[3]),"+f"(d[4]),"+f"(d[5]),"+f"(d[6]),"+f"(d[7]),"+f"(d[8]),"+f"(d[9]),"+f"(d[10]),"+f"(d[11]),"+f"(d[12]),"+f"(d[13]),"+f"(d[14]),"+f"(d[15]),"+f"(d[16]),"+f"(d[17]),"+f"(d[18]),"+f"(d[19]),"+f"(d[20]),"+f"(d[21]),"+f"(d[22]),"+f"(d[23]) : "r"(a0),"r"(a1),"r"(a2),"r"(a3),"l"(b),"r"(sc),"n"(TB));
  }
};
template<> struct WG<56> {
  template<int TB> static __device__ __forceinline__ void rs(float* d, uint32_t a0, uint32_t a1, uint32_t a2, uint32_t a3, uint64_t b, int sc) {
    asm volatile("{.reg .pred p; setp.ne.b32 p, %33, 0; wgmma.mma_async.sync.aligned.m64n56k16.f32.bf16.bf16 {%0,%1,%2,%3,%4,%5,%6,%7,%8,%9,%10,%11,%12,%13,%14,%15,%16,%17,%18,%19,%20,%21,%22,%23,%24,%25,%26,%27},{%28,%29,%30,%31},%32,p,1,1,%34;}"
      : "+f"(d[0]),"+f"(d[1]),"+f"(d[2]),"+f"(d[3]),"+f"(d[4]),"+f"(d[5]),"+f"(d[6]),"+f"(d[7]),"+f"(d[8]),"+f"(d[9]),"+f"(d[10]),"+f"(d[11]),"+f"(d[12]),"+f"(d[13]),"+f"(d[14]),"+f"(d[15]),"+f"(d[16]),"+f"(d[17]),"+f"(d[18]),"+f"(d[19]),"+f"(d[20]),"+f"(d[21]),"+f"(d[22]),"+f"(d[23]),"+f"(d[24]),"+f"(d[25]),"+f"(d[26]),"+f"(d[27]) : "r"(a0),"r"(a1),"r"(a2),"r"(a3),"l"(b),"r"(sc),"n"(TB));
  }
};
template<> struct WG<64> {
  template<int TB> static __device__ __forceinline__ void rs(float* d, uint32_t a0, uint32_t a1, uint32_t a2, uint32_t a3, uint64_t b, int sc) {
    asm volatile("{.reg .pred p; setp.ne.b32 p, %37, 0; wgmma.mma_async.sync.aligned.m64n64k16.f32.bf16.bf16 {%0,%1,%2,%3,%4,%5,%6,%7,%8,%9,%10,%11,%12,%13,%14,%15,%16,%17,%18,%19,%20,%21,%22,%23,%24,%25,%26,%27,%28,%29,%30,%31},{%32,%33,%34,%35},%36,p,1,1,%38;}"
      : "+f"(d[0]),"+f"(d[1]),"+f"(d[2]),"+f"(d[3]),"+f"(d[4]),"+f"(d[5]),"+f"(d[6]),"+f"(d[7]),"+f"(d[8]),"+f"(d[9]),"+f"(d[10]),"+f"(d[11]),"+f"(d[12]),"+f"(d[13]),"+f"(d[14]),"+f"(d[15]),"+f"(d[16]),"+f"(d[17]),"+f"(d[18]),"+f"(d[19]),"+f"(d[20]),"+f"(d[21]),"+f"(d[22]),"+f"(d[23]),"+f"(d[24]),"+f"(d[25]),"+f"(d[26]),"+f"(d[27]),"+f"(d[28]),"+f"(d[29]),"+f"(d[30]),"+f"(d[31]) : "r"(a0),"r"(a1),"r"(a2),"r"(a3),"l"(b),"r"(sc),"n"(TB));
  }
};
template<> struct WG<72> {
  template<int TB> static __device__ __forceinline__ void rs(float* d, uint32_t a0, uint32_t a1, uint32_t a2, uint32_t a3, uint64_t b, int sc) {
    asm volatile("{.reg .pred p; setp.ne.b32 p, %41, 0; wgmma.mma_async.sync.aligned.m64n72k16.f32.bf16.bf16 {%0,%1,%2,%3,%4,%5,%6,%7,%8,%9,%10,%11,%12,%13,%14,%15,%16,%17,%18,%19,%20,%21,%22,%23,%24,%25,%26,%27,%28,%29,%30,%31,%32,%33,%34,%35},{%36,%37,%38,%39},%40,p,1,1,%42;}"
      : "+f"(d[0]),"+f"(d[1]),"+f"(d[2]),"+f"(d[3]),"+f"(d[4]),"+f"(d[5]),"+f"(d[6]),"+f"(d[7]),"+f"(d[8]),"+f"(d[9]),"+f"(d[10]),"+f"(d[11]),"+f"(d[12]),"+f"(d[13]),"+f"(d[14]),"+f"(d[15]),"+f"(d[16]),"+f"(d[17]),"+f"(d[18]),"+f"(d[19]),"+f"(d[20]),"+f"(d[21]),"+f"(d[22]),"+f"(d[23]),"+f"(d[24]),"+f"(d[25]),"+f"(d[26]),"+f"(d[27]),"+f"(d[28]),"+f"(d[29]),"+f"(d[30]),"+f"(d[31]),"+f"(d[32]),"+f"(d[33]),"+f"(d[34]),"+f"(d[35]) : "r"(a0),"r"(a1),"r"(a2),"r"(a3),"l"(b),"r"(sc),"n"(TB));
  }
};
template<> struct WG<80> {
  template<int TB> static __device__ __forceinline__ void rs(float* d, uint32_t a0, uint32_t a1, uint32_t a2, uint32_t a3, uint64_t b, int sc) {
    asm volatile("{.reg .pred p; setp.ne.b32 p, %45, 0; wgmma.mma_async.sync.aligned.m64n80k16.f32.bf16.bf16 {%0,%1,%2,%3,%4,%5,%6,%7,%8,%9,%10,%11,%12,%13,%14,%15,%16,%17,%18,%19,%20,%21,%22,%23,%24,%25,%26,%27,%28,%29,%30,%31,%32,%33,%34,%35,%36,%37,%38,%39},{%40,%41,%42,%43},%44,p,1,1,%46;}"
      : "+f"(d[0]),"+f"(d[1]),"+f"(d[2]),"+f"(d[3]),"+f"(d[4]),"+f"(d[5]),"+f"(d[6]),"+f"(d[7]),"+f"(d[8]),"+f"(d[9]),"+f"(d[10]),"+f"(d[11]),"+f"(d[12]),"+f"(d[13]),"+f"(d[14]),"+f"(d[15]),"+f"(d[16]),"+f"(d[17]),"+f"(d[18]),"+f"(d[19]),"+f"(d[20]),"+f"(d[21]),"+f"(d[22]),"+f"(d[23]),"+f"(d[24]),"+f"(d[25]),"+f"(d[26]),"+f"(d[27]),"+f"(d[28]),"+f"(d[29]),"+f"(d[30]),"+f"(d[31]),"+f"(d[32]),"+f"(d[33]),"+f"(d[34]),"+f"(d[35]),"+f"(d[36]),"+f"(d[37]),"+f"(d[38]),"+f"(d[39]) : "r"(a0),"r"(a1),"r"(a2),"r"(a3),"l"(b),"r"(sc),"n"(TB));
  }
};
template<> struct WG<88> {
  template<int TB> static __device__ __forceinline__ void rs(float* d, uint32_t a0, uint32_t a1, uint32_t a2, uint32_t a3, uint64_t b, int sc) {
    asm volatile("{.reg .pred p; setp.ne.b32 p, %49, 0; wgmma.mma_async.sync.aligned.m64n88k16.f32.bf16.bf16 {%0,%1,%2,%3,%4,%5,%6,%7,%8,%9,%10,%11,%12,%13,%14,%15,%16,%17,%18,%19,%20,%21,%22,%23,%24,%25,%26,%27,%28,%29,%30,%31,%32,%33,%34,%35,%36,%37,%38,%39,%40,%41,%42,%43},{%44,%45,%46,%47},%48,p,1,1,%50;}"
      : "+f"(d[0]),"+f"(d[1]),"+f"(d[2]),"+f"(d[3]),"+f"(d[4]),"+f"(d[5]),"+f"(d[6]),"+f"(d[7]),"+f"(d[8]),"+f"(d[9]),"+f"(d[10]),"+f"(d[11]),"+f"(d[12]),"+f"(d[13]),"+f"(d[14]),"+f"(d[15]),"+f"(d[16]),"+f"(d[17]),"+f"(d[18]),"+f"(d[19]),"+f"(d[20]),"+f"(d[21]),"+f"(d[22]),"+f"(d[23]),"+f"(d[24]),"+f"(d[25]),"+f"(d[26]),"+f"(d[27]),"+f"(d[28]),"+f"(d[29]),"+f"(d[30]),"+f"(d[31]),"+f"(d[32]),"+f"(d[33]),"+f"(d[34]),"+f"(d[35]),"+f"(d[36]),"+f"(d[37]),"+f"(d[38]),"+f"(d[39]),"+f"(d[40]),"+f"(d[41]),"+f"(d[42]),"+f"(d[43]) : "r"(a0),"r"(a1),"r"(a2),"r"(a3),"l"(b),"r"(sc),"n"(TB));
  }
};
template<> struct WG<96> {
  template<int TB> static __device__ __forceinline__ void rs(float* d, uint32_t a0, uint32_t a1, uint32_t a2, uint32_t a3, uint64_t b, int sc) {
    asm volatile("{.reg .pred p; setp.ne.b32 p, %53, 0; wgmma.mma_async.sync.aligned.m64n96k16.f32.bf16.bf16 {%0,%1,%2,%3,%4,%5,%6,%7,%8,%9,%10,%11,%12,%13,%14,%15,%16,%17,%18,%19,%20,%21,%22,%23,%24,%25,%26,%27,%28,%29,%30,%31,%32,%33,%34,%35,%36,%37,%38,%39,%40,%41,%42,%43,%44,%45,%46,%47},{%48,%49,%50,%51},%52,p,1,1,%54;}"
      : "+f"(d[0]),"+f"(d[1]),"+f"(d[2]),"+f"(d[3]),"+f"(d[4]),"+f"(d[5]),"+f"(d[6]),"+f"(d[7]),"+f"(d[8]),"+f"(d[9]),"+f"(d[10]),"+f"(d[11]),"+f"(d[12]),"+f"(d[13]),"+f"(d[14]),"+f"(d[15]),"+f"(d[16]),"+f"(d[17]),"+f"(d[18]),"+f"(d[19]),"+f"(d[20]),"+f"(d[21]),"+f"(d[22]),"+f"(d[23]),"+f"(d[24]),"+f"(d[25]),"+f"(d[26]),"+f"(d[27]),"+f"(d[28]),"+f"(d[29]),"+f"(d[30]),"+f"(d[31]),"+f"(d[32]),"+f"(d[33]),"+f"(d[34]),"+f"(d[35]),"+f"(d[36]),"+f"(d[37]),"+f"(d[38]),"+f"(d[39]),"+f"(d[40]),"+f"(d[41]),"+f"(d[42]),"+f"(d[43]),"+f"(d[44]),"+f"(d[45]),"+f"(d[46]),"+f"(d[47]) : "r"(a0),"r"(a1),"r"(a2),"r"(a3),"l"(b),"r"(sc),"n"(TB));
  }
};
template<> struct WG<104> {
  template<int TB> static __device__ __forceinline__ void rs(float* d, uint32_t a0, uint32_t a1, uint32_t a2, uint32_t a3, uint64_t b, int sc) {
    asm volatile("{.reg .pred p; setp.ne.b32 p, %57, 0; wgmma.mma_async.sync.aligned.m64n104k16.f32.bf16.bf16 {%0,%1,%2,%3,%4,%5,%6,%7,%8,%9,%10,%11,%12,%13,%14,%15,%16,%17,%18,%19,%20,%21,%22,%23,%24,%25,%26,%27,%28,%29,%30,%31,%32,%33,%34,%35,%36,%37,%38,%39,%40,%41,%42,%43,%44,%45,%46,%47,%48,%49,%50,%51},{%52,%53,%54,%55},%56,p,1,1,%58;}"
      : "+f"(d[0]),"+f"(d[1]),"+f"(d[2]),"+f"(d[3]),"+f"(d[4]),"+f"(d[5]),"+f"(d[6]),"+f"(d[7]),"+f"(d[8]),"+f"(d[9]),"+f"(d[10]),"+f"(d[11]),"+f"(d[12]),"+f"(d[13]),"+f"(d[14]),"+f"(d[15]),"+f"(d[16]),"+f"(d[17]),"+f"(d[18]),"+f"(d[19]),"+f"(d[20]),"+f"(d[21]),"+f"(d[22]),"+f"(d[23]),"+f"(d[24]),"+f"(d[25]),"+f"(d[26]),"+f"(d[27]),"+f"(d[28]),"+f"(d[29]),"+f"(d[30]),"+f"(d[31]),"+f"(d[32]),"+f"(d[33]),"+f"(d[34]),"+f"(d[35]),"+f"(d[36]),"+f"(d[37]),"+f"(d[38]),"+f"(d[39]),"+f"(d[40]),"+f"(d[41]),"+f"(d[42]),"+f"(d[43]),"+f"(d[44]),"+f"(d[45]),"+f"(d[46]),"+f"(d[47]),"+f"(d[48]),"+f"(d[49]),"+f"(d[50]),"+f"(d[51]) : "r"(a0),"r"(a1),"r"(a2),"r"(a3),"l"(b),"r"(sc),"n"(TB));
  }
};
template<> struct WG<112> {
  template<int TB> static __device__ __forceinline__ void rs(float* d, uint32_t a0, uint32_t a1, uint32_t a2, uint32_t a3, uint64_t b, int sc) {
    asm volatile("{.reg .pred p; setp.ne.b32 p, %61, 0; wgmma.mma_async.sync.aligned.m64n112k16.f32.bf16.bf16 {%0,%1,%2,%3,%4,%5,%6,%7,%8,%9,%10,%11,%12,%13,%14,%15,%16,%17,%18,%19,%20,%21,%22,%23,%24,%25,%26,%27,%28,%29,%30,%31,%32,%33,%34,%35,%36,%37,%38,%39,%40,%41,%42,%43,%44,%45,%46,%47,%48,%49,%50,%51,%52,%53,%54,%55},{%56,%57,%58,%59},%60,p,1,1,%62;}"
      : "+f"(d[0]),"+f"(d[1]),"+f"(d[2]),"+f"(d[3]),"+f"(d[4]),"+f"(d[5]),"+f"(d[6]),"+f"(d[7]),"+f"(d[8]),"+f"(d[9]),"+f"(d[10]),"+f"(d[11]),"+f"(d[12]),"+f"(d[13]),"+f"(d[14]),"+f"(d[15]),"+f"(d[16]),"+f"(d[17]),"+f"(d[18]),"+f"(d[19]),"+f"(d[20]),"+f"(d[21]),"+f"(d[22]),"+f"(d[23]),"+f"(d[24]),"+f"(d[25]),"+f"(d[26]),"+f"(d[27]),"+f"(d[28]),"+f"(d[29]),"+f"(d[30]),"+f"(d[31]),"+f"(d[32]),"+f"(d[33]),"+f"(d[34]),"+f"(d[35]),"+f"(d[36]),"+f"(d[37]),"+f"(d[38]),"+f"(d[39]),"+f"(d[40]),"+f"(d[41]),"+f"(d[42]),"+f"(d[43]),"+f"(d[44]),"+f"(d[45]),"+f"(d[46]),"+f"(d[47]),"+f"(d[48]),"+f"(d[49]),"+f"(d[50]),"+f"(d[51]),"+f"(d[52]),"+f"(d[53]),"+f"(d[54]),"+f"(d[55]) : "r"(a0),"r"(a1),"r"(a2),"r"(a3),"l"(b),"r"(sc),"n"(TB));
  }
};
template<> struct WG<120> {
  template<int TB> static __device__ __forceinline__ void rs(float* d, uint32_t a0, uint32_t a1, uint32_t a2, uint32_t a3, uint64_t b, int sc) {
    asm volatile("{.reg .pred p; setp.ne.b32 p, %65, 0; wgmma.mma_async.sync.aligned.m64n120k16.f32.bf16.bf16 {%0,%1,%2,%3,%4,%5,%6,%7,%8,%9,%10,%11,%12,%13,%14,%15,%16,%17,%18,%19,%20,%21,%22,%23,%24,%25,%26,%27,%28,%29,%30,%31,%32,%33,%34,%35,%36,%37,%38,%39,%40,%41,%42,%43,%44,%45,%46,%47,%48,%49,%50,%51,%52,%53,%54,%55,%56,%57,%58,%59},{%60,%61,%62,%63},%64,p,1,1,%66;}"
      : "+f"(d[0]),"+f"(d[1]),"+f"(d[2]),"+f"(d[3]),"+f"(d[4]),"+f"(d[5]),"+f"(d[6]),"+f"(d[7]),"+f"(d[8]),"+f"(d[9]),"+f"(d[10]),"+f"(d[11]),"+f"(d[12]),"+f"(d[13]),"+f"(d[14]),"+f"(d[15]),"+f"(d[16]),"+f"(d[17]),"+f"(d[18]),"+f"(d[19]),"+f"(d[20]),"+f"(d[21]),"+f"(d[22]),"+f"(d[23]),"+f"(d[24]),"+f"(d[25]),"+f"(d[26]),"+f"(d[27]),"+f"(d[28]),"+f"(d[29]),"+f"(d[30]),"+f"(d[31]),"+f"(d[32]),"+f"(d[33]),"+f"(d[34]),"+f"(d[35]),"+f"(d[36]),"+f"(d[37]),"+f"(d[38]),"+f"(d[39]),"+f"(d[40]),"+f"(d[41]),"+f"(d[42]),"+f"(d[43]),"+f"(d[44]),"+f"(d[45]),"+f"(d[46]),"+f"(d[47]),"+f"(d[48]),"+f"(d[49]),"+f"(d[50]),"+f"(d[51]),"+f"(d[52]),"+f"(d[53]),"+f"(d[54]),"+f"(d[55]),"+f"(d[56]),"+f"(d[57]),"+f"(d[58]),"+f"(d[59]) : "r"(a0),"r"(a1),"r"(a2),"r"(a3),"l"(b),"r"(sc),"n"(TB));
  }
};
template<> struct WG<128> {
  template<int TB> static __device__ __forceinline__ void rs(float* d, uint32_t a0, uint32_t a1, uint32_t a2, uint32_t a3, uint64_t b, int sc) {
    asm volatile("{.reg .pred p; setp.ne.b32 p, %69, 0; wgmma.mma_async.sync.aligned.m64n128k16.f32.bf16.bf16 {%0,%1,%2,%3,%4,%5,%6,%7,%8,%9,%10,%11,%12,%13,%14,%15,%16,%17,%18,%19,%20,%21,%22,%23,%24,%25,%26,%27,%28,%29,%30,%31,%32,%33,%34,%35,%36,%37,%38,%39,%40,%41,%42,%43,%44,%45,%46,%47,%48,%49,%50,%51,%52,%53,%54,%55,%56,%57,%58,%59,%60,%61,%62,%63},{%64,%65,%66,%67},%68,p,1,1,%70;}"
      : "+f"(d[0]),"+f"(d[1]),"+f"(d[2]),"+f"(d[3]),"+f"(d[4]),"+f"(d[5]),"+f"(d[6]),"+f"(d[7]),"+f"(d[8]),"+f"(d[9]),"+f"(d[10]),"+f"(d[11]),"+f"(d[12]),"+f"(d[13]),"+f"(d[14]),"+f"(d[15]),"+f"(d[16]),"+f"(d[17]),"+f"(d[18]),"+f"(d[19]),"+f"(d[20]),"+f"(d[21]),"+f"(d[22]),"+f"(d[23]),"+f"(d[24]),"+f"(d[25]),"+f"(d[26]),"+f"(d[27]),"+f"(d[28]),"+f"(d[29]),"+f"(d[30]),"+f"(d[31]),"+f"(d[32]),"+f"(d[33]),"+f"(d[34]),"+f"(d[35]),"+f"(d[36]),"+f"(d[37]),"+f"(d[38]),"+f"(d[39]),"+f"(d[40]),"+f"(d[41]),"+f"(d[42]),"+f"(d[43]),"+f"(d[44]),"+f"(d[45]),"+f"(d[46]),"+f"(d[47]),"+f"(d[48]),"+f"(d[49]),"+f"(d[50]),"+f"(d[51]),"+f"(d[52]),"+f"(d[53]),"+f"(d[54]),"+f"(d[55]),"+f"(d[56]),"+f"(d[57]),"+f"(d[58]),"+f"(d[59]),"+f"(d[60]),"+f"(d[61]),"+f"(d[62]),"+f"(d[63]) : "r"(a0),"r"(a1),"r"(a2),"r"(a3),"l"(b),"r"(sc),"n"(TB));
  }
};

constexpr int STG = 57344, XB = 32768, W_TX = 18432;
constexpr int MBS = 16384;
constexpr int OFF_WO = 69632;
constexpr int OFF_KTAB = 172032;
constexpr int KTS = 4128;
constexpr int OFF_PRM = OFF_KTAB + 5 * KTS - 5120;
constexpr int OFF_U = OFF_KTAB + 20736;
constexpr int US = 4224, UPL = 2112;
constexpr int OFF_B2 = OFF_U + 2 * US;
constexpr int OFF_P = OFF_KTAB + 36864;
constexpr int OFF_KA = OFF_U, OFF_KT = OFF_KA + 28672;
constexpr int OFF_WPHI = OFF_P + 16896 + 1280;
constexpr int OFF_BAR = OFF_WPHI + 3840;
constexpr int SMEM_BYTES = OFF_BAR + 512;
constexpr int B_FULL = 0, B_EMPTY = 24, B_WO = 48, B_U = 56, B_BT = 72, B_EP = 80, B_P1 = 88, B_UE = 96, B_CD = 112, B_XW = 120, B_KG = 160, B_KU = 168, B_KVD = 176, B_W2 = 184, O_EPOCH = 192;
#define CW 1
#define CW0 12
#define P1POS 0
#define CBV 3
constexpr int CB0 = CBV == 0 ? 3 : CBV == 1 ? 6 : 4;
#define POLL 0
#define SIG 1
#define DLY 2
#define NBV 5
#define WO0 0
#define EARLY 0
constexpr int S_U = 256;
constexpr int S_B = S_U + 640 * 256;
constexpr int S_O = S_B + 16 * 8 * 80 * 16;
constexpr int S_KV = S_O + 32 * 8 * 640;
constexpr int S_END = (S_KV + 16 * 8 * 264 + 255) / 256 * 256;
__device__ __align__(4096) uint4 g_s[S_END + 256];
#define TS(i) do {} while (0)

__device__ __forceinline__ void mbar_init(uint32_t b, int c) { asm volatile("mbarrier.init.shared::cta.b64 [%0], %1;" ::"r"(b), "r"(c) : "memory"); }
__device__ __forceinline__ void mbar_expect(uint32_t b, int bytes) { asm volatile("mbarrier.arrive.expect_tx.shared::cta.b64 _, [%0], %1;" ::"r"(b), "r"(bytes) : "memory"); }
__device__ __forceinline__ void mbar_arrive(uint32_t b) { asm volatile("mbarrier.arrive.shared::cta.b64 _, [%0];" ::"r"(b) : "memory"); }
__device__ __forceinline__ void mbar_wait_(uint32_t b, int ph, int& n) {
  asm volatile("{\n.reg .pred p;\nLW%=:\nmbarrier.try_wait.parity.shared::cta.b64 p, [%1], %2;\nadd.s32 %0, %0, -1;\nsetp.gt.and.s32 p, %0, 0, !p;\n@p bra LW%=;\n}" : "+r"(n) : "r"(b), "r"(ph) : "memory");
}
#define mbar_wait(b, ph) mbar_wait_(b, ph, budget)
__device__ __forceinline__ void cnt_wait_(const unsigned* p, unsigned target, int& n) {
  asm volatile("{\n.reg .pred p;\n.reg .s32 v;\nLW%=:\nld.acquire.gpu.global.u32 v, [%1];\nadd.s32 %0, %0, -16;\nsetp.gt.s32 p, %0, 0;\nsub.s32 v, v, %2;\nsetp.lt.and.s32 p, v, 0, p;\n@p bra LW%=;\n}" : "+r"(n) : "l"(p), "r"(target) : "memory");
}
#define cnt_wait(p, t) cnt_wait_(p, t, budget)
__device__ __forceinline__ void cnt_release(unsigned* p) {
  asm volatile("fence.acq_rel.gpu;\nred.relaxed.gpu.global.add.u32 [%0], 1;" ::"l"(p) : "memory");
}
__device__ __forceinline__ void cnt_poll_(const unsigned* p, unsigned target, int& n) {
  asm volatile("{\n.reg .pred p;\n.reg .s32 v;\nLW%=:\nld.relaxed.gpu.global.u32 v, [%1];\nadd.s32 %0, %0, -16;\nsetp.gt.s32 p, %0, 0;\nsub.s32 v, v, %2;\nsetp.lt.and.s32 p, v, 0, p;\n@p bra LW%=;\n}" : "+r"(n) : "l"(p), "r"(target) : "memory");
}
#define cnt_poll(p, t) cnt_poll_(p, t, budget)
__device__ __forceinline__ void cnt_add(unsigned* p, int lane) { asm volatile("{\n.reg .pred p;\nsetp.eq.s32 p, %1, 0;\n@p red.relaxed.gpu.global.add.u32 [%0], 1;\n}" ::"l"(p), "r"(lane) : "memory"); }
template <class T> __device__ __forceinline__ void pin(T*& p) { asm volatile("" : "+l"(p)::"memory"); }
__device__ __forceinline__ void pin(uint32_t& v) { asm volatile("" : "+r"(v)::"memory"); }
__device__ __forceinline__ uint32_t tag2(uint32_t a, uint32_t b, uint32_t e) { uint32_t r; asm volatile("lop3.b32 %0, %1, %2, %3, 0x7E;" : "=r"(r) : "r"(a), "r"(b), "r"(e)); return r; }
__device__ __forceinline__ uint32_t or3(uint32_t a, uint32_t b, uint32_t c) { uint32_t r; asm volatile("lop3.b32 %0, %1, %2, %3, 0xFE;" : "=r"(r) : "r"(a), "r"(b), "r"(c)); return r; }
__device__ __forceinline__ uint32_t settag(uint32_t a, uint32_t e) { uint32_t r; asm("lop3.b32 %0, %1, %2, 1, 0xD8;" : "=r"(r) : "r"(a), "r"(e)); return r; }
__device__ __forceinline__ bool bar_or(int id, int n, bool v) {
  uint32_t r;
  asm volatile("{\n.reg .pred p, q;\nsetp.ne.u32 p, %3, 0;\nbarrier.cta.red.or.aligned.pred q, %1, %2, p;\nselp.u32 %0, 1, 0, q;\n}" : "=r"(r) : "r"(id), "r"(n), "r"((uint32_t)v) : "memory");
  return r != 0;
}
__device__ __forceinline__ void tma5(uint32_t dst, const CUtensorMap* m, int c0, uint32_t bar) {
  asm volatile("cp.async.bulk.tensor.5d.shared::cluster.global.mbarrier::complete_tx::bytes [%0], [%1, {%3,%4,%4,%4,%4}], [%2];" ::"r"(dst), "l"(m), "r"(bar), "r"(c0), "r"(0) : "memory");
}
__device__ __forceinline__ void bar_sync(int id, int n) { asm volatile("bar.sync %0, %1;" ::"r"(id), "r"(n) : "memory"); }
__device__ __forceinline__ void bar_arrive(int id, int n) { asm volatile("bar.arrive %0, %1;" ::"r"(id), "r"(n) : "memory"); }
__device__ __forceinline__ void fence_async_smem() { asm volatile("fence.proxy.async.shared::cta;" ::: "memory"); }
__device__ __forceinline__ void fence_async_all() { asm volatile("fence.proxy.async;" ::: "memory"); }
__device__ __forceinline__ void tma2(uint32_t dst, const CUtensorMap* m, int c0, int c1, uint32_t bar) {
  asm volatile("cp.async.bulk.tensor.2d.shared::cluster.global.mbarrier::complete_tx::bytes [%0], [%1, {%3,%4}], [%2];" ::"r"(dst), "l"(m), "r"(bar), "r"(c0), "r"(c1) : "memory");
}
__device__ __forceinline__ void tma3(uint32_t dst, const CUtensorMap* m, int c0, int c1, int c2, uint32_t bar) {
  asm volatile("cp.async.bulk.tensor.3d.shared::cluster.global.mbarrier::complete_tx::bytes [%0], [%1, {%3,%4,%5}], [%2];" ::"r"(dst), "l"(m), "r"(bar), "r"(c0), "r"(c1), "r"(c2) : "memory");
}
__device__ __forceinline__ void tma_store2(const CUtensorMap* m, uint32_t src, int c0, int c1) {
  asm volatile("cp.async.bulk.tensor.2d.global.shared::cta.bulk_group [%0, {%2,%3}], [%1];" ::"l"(m), "r"(src), "r"(c0), "r"(c1) : "memory");
}
__device__ __forceinline__ void bulk(uint32_t dst, const void* src, int bytes, uint32_t bar) {
  asm volatile("cp.async.bulk.shared::cluster.global.mbarrier::complete_tx::bytes [%0], [%1], %2, [%3];" ::"r"(dst), "l"(src), "r"(bytes), "r"(bar) : "memory");
}
__device__ __forceinline__ uint64_t mkdesc(uint32_t addr, uint32_t lbo, uint32_t sbo, int sw) {
  return (uint64_t)((addr & 0x3FFFF) >> 4) | ((uint64_t)(lbo >> 4) << 16) | ((uint64_t)(sbo >> 4) << 32) | ((uint64_t)sw << 62);
}
__device__ __forceinline__ void wg_fence() { asm volatile("wgmma.fence.sync.aligned;" ::: "memory"); }
__device__ __forceinline__ void wg_commit() { asm volatile("wgmma.commit_group.sync.aligned;" ::: "memory"); }
template <int N> __device__ __forceinline__ void fence_regs(float* d) {
#pragma unroll
  for (int i = 0; i < N; i++) asm volatile("" : "+f"(d[i])::"memory");
}
template <int N> __device__ __forceinline__ void wg_wait() { asm volatile("wgmma.wait_group.sync.aligned %0;" ::"n"(N) : "memory"); }
__device__ __forceinline__ void ldsm4t(uint32_t* r, uint32_t a) { asm volatile("ldmatrix.sync.aligned.m8n8.x4.trans.shared.b16 {%0,%1,%2,%3}, [%4];" : "=r"(r[0]), "=r"(r[1]), "=r"(r[2]), "=r"(r[3]) : "r"(a) : "memory"); }
__device__ __forceinline__ void stsm4(uint32_t a, uint32_t r0, uint32_t r1, uint32_t r2, uint32_t r3) { asm volatile("stmatrix.sync.aligned.m8n8.x4.shared.b16 [%0], {%1,%2,%3,%4};" ::"r"(a), "r"(r0), "r"(r1), "r"(r2), "r"(r3) : "memory"); }
__device__ __forceinline__ void stsm4t(uint32_t a, uint32_t r0, uint32_t r1, uint32_t r2, uint32_t r3) { asm volatile("stmatrix.sync.aligned.m8n8.x4.trans.shared.b16 [%0], {%1,%2,%3,%4};" ::"r"(a), "r"(r0), "r"(r1), "r"(r2), "r"(r3) : "memory"); }
__device__ __forceinline__ uint32_t pack(float lo, float hi) { uint32_t r; asm("cvt.rn.bf16x2.f32 %0, %1, %2;" : "=r"(r) : "f"(hi), "f"(lo)); return r; }
__device__ __forceinline__ float bf_lo(uint32_t w) { return __uint_as_float(w << 16); }
__device__ __forceinline__ float ex2(float x) { float r; asm("ex2.approx.ftz.f32 %0, %1;" : "=f"(r) : "f"(x)); return r; }
__device__ __forceinline__ float rcp(float x) { float r; asm("rcp.approx.ftz.f32 %0, %1;" : "=f"(r) : "f"(x)); return r; }
__device__ __forceinline__ uint32_t lds32(uint32_t a) { uint32_t v; asm volatile("ld.shared.u32 %0, [%1];" : "=r"(v) : "r"(a) : "memory"); return v; }
__device__ __forceinline__ uint32_t lds16(uint32_t a) { uint32_t v; asm volatile("ld.shared.u16 %0, [%1];" : "=r"(v) : "r"(a) : "memory"); return v; }
__device__ __forceinline__ uint4 lds128(uint32_t a) { uint4 v; asm volatile("ld.shared.v4.u32 {%0,%1,%2,%3}, [%4];" : "=r"(v.x), "=r"(v.y), "=r"(v.z), "=r"(v.w) : "r"(a) : "memory"); return v; }
__device__ __forceinline__ void lds128p(uint4& v, uint32_t a, int n) { asm volatile("{\n.reg .pred q;\nsetp.ge.s32 q, %5, 0;\n@q ld.shared.v4.u32 {%0,%1,%2,%3}, [%4];\n}" : "+r"(v.x), "+r"(v.y), "+r"(v.z), "+r"(v.w) : "r"(a), "r"(n) : "memory"); }
__device__ __forceinline__ void sts32(uint32_t a, uint32_t v) { asm volatile("st.shared.u32 [%0], %1;" ::"r"(a), "r"(v) : "memory"); }
__device__ __forceinline__ void sts64f(uint32_t a, float x, float y) { asm volatile("st.shared.v2.f32 [%0], {%1,%2};" ::"r"(a), "f"(x), "f"(y) : "memory"); }
__device__ __forceinline__ void sts128(uint32_t a, uint4 v) { asm volatile("st.shared.v4.u32 [%0], {%1,%2,%3,%4};" ::"r"(a), "r"(v.x), "r"(v.y), "r"(v.z), "r"(v.w) : "memory"); }
__device__ __forceinline__ uint4 ldg128(const void* p) { uint4 v; asm volatile("ld.relaxed.gpu.global.v4.u32 {%0,%1,%2,%3}, [%4];" : "=r"(v.x), "=r"(v.y), "=r"(v.z), "=r"(v.w) : "l"(p) : "memory"); return v; }
#define LDM "ld.relaxed.gpu.global"
__device__ __forceinline__ uint4 ldg128w(const void* p) { uint4 v; asm volatile(LDM ".v4.u32 {%0,%1,%2,%3}, [%4];" : "=r"(v.x), "=r"(v.y), "=r"(v.z), "=r"(v.w) : "l"(p) : "memory"); return v; }
__device__ __forceinline__ void ldg128t(uint4& v, const void* p, uint32_t e) { asm volatile("{\n.reg .pred q;\n.reg .b32 t;\nlop3.b32 t, %0, %5, 1, 0x28;\nsetp.ne.u32 q, t, 0;\n@q ld.relaxed.gpu.global.v4.u32 {%0,%1,%2,%3}, [%4];\n}" : "+r"(v.x), "+r"(v.y), "+r"(v.z), "+r"(v.w) : "l"(p), "r"(e) : "memory"); }
__device__ __forceinline__ void undef(uint4& v, uint32_t e) { v.x = ~e; asm volatile("" : "=r"(v.y), "=r"(v.z), "=r"(v.w)); }
__device__ __forceinline__ void stg128(void* p, uint32_t a, uint32_t b, uint32_t c, uint32_t d) { asm volatile("st.relaxed.gpu.global.v4.u32 [%0], {%1,%2,%3,%4};" ::"l"(p), "r"(a), "r"(b), "r"(c), "r"(d) : "memory"); }
__device__ __forceinline__ void stg64(void* p, uint32_t a, uint32_t b) { asm volatile("st.relaxed.gpu.global.v2.u32 [%0], {%1,%2};" ::"l"(p), "r"(a), "r"(b) : "memory"); }
__device__ __forceinline__ uint32_t hadd2(uint32_t a, uint32_t b) { uint32_t r; asm("add.rn.bf16x2 %0, %1, %2;" : "=r"(r) : "r"(a), "r"(b)); return r; }
__device__ __forceinline__ float bfr(float x) { return __uint_as_float(pack(0.f, x)); }
struct cplx { float r, i; };
__device__ __forceinline__ cplx cmul(cplx a, cplx b) { cplx c; c.r = a.r * b.r - a.i * b.i; c.i = a.r * b.i + a.i * b.r; return c; }
__device__ __forceinline__ cplx csq(cplx a) { cplx c; c.r = a.r * a.r - a.i * a.i; c.i = 2.f * a.r * a.i; return c; }
__device__ __forceinline__ cplx cexp2(float re2, float im) { const float e = ex2(re2); return cplx{e * __cosf(im), e * __sinf(im)}; }
__device__ __forceinline__ uint32_t hmul2(uint32_t a, uint32_t b) { uint32_t r; asm("mul.rn.bf16x2 %0, %1, %2;" : "=r"(r) : "r"(a), "r"(b)); return r; }
__device__ __forceinline__ uint32_t hfma2(uint32_t a, uint32_t b, uint32_t c) { uint32_t r; asm("fma.rn.bf16x2 %0, %1, %2, %3;" : "=r"(r) : "r"(a), "r"(b), "r"(c)); return r; }
__device__ __forceinline__ void hcmul(uint32_t& ore, uint32_t& oim, uint32_t re, uint32_t im, uint32_t m) {
  asm("{\n.reg .b16 l, h, n;\n.reg .b32 rr, ii, nn, t, u;\nmov.b32 {l, h}, %4;\nmov.b32 {_, n}, %5;\nmov.b32 rr, {l, l};\nmov.b32 ii, {h, h};\nmov.b32 nn, {n, n};\n"
      "mul.rn.bf16x2 t, %3, nn;\nmul.rn.bf16x2 u, %3, rr;\nfma.rn.bf16x2 t, %2, rr, t;\nfma.rn.bf16x2 %1, %2, ii, u;\nmov.b32 %0, t;\n}"
      : "=r"(ore), "=r"(oim) : "r"(re), "r"(im), "r"(m), "r"(m ^ 0x80000000u));
}
__device__ __forceinline__ void sts128x(uint32_t a, uint32_t x, uint32_t y, uint32_t z) { asm volatile("{\n.reg .b32 u;\nst.shared.v4.u32 [%0], {%1,%2,%3,u};\n}" ::"r"(a), "r"(x), "r"(y), "r"(z) : "memory"); }
__device__ __forceinline__ uint32_t ldu16(const __nv_bfloat16* p) { return __ldg((const unsigned short*)p); }
__device__ __forceinline__ void stsf(uint32_t a, float v) { asm volatile("st.shared.f32 [%0], %1;" ::"r"(a), "f"(v) : "memory"); }
__device__ __forceinline__ void sts64(uint32_t a, uint32_t x, uint32_t y) { asm volatile("st.shared.v2.u32 [%0], {%1,%2};" ::"r"(a), "r"(x), "r"(y) : "memory"); }
__device__ __forceinline__ float ldsum(uint32_t a) { return __uint_as_float(lds32(a)) + __uint_as_float(lds32(a + 2688)); }
__device__ __forceinline__ uint2 lds64(uint32_t a) { uint2 v; asm volatile("ld.shared.v2.u32 {%0,%1}, [%2];" : "=r"(v.x), "=r"(v.y) : "r"(a) : "memory"); return v; }

__device__ __forceinline__ void dual_exp(const float* p, float* e) {
  constexpr float L2E = 1.4426950408889634f;
  float mx = p[0], mn = p[0];
#pragma unroll
  for (int i = 1; i < 10; i++) { float v = p[4 * (i >> 1) + (i & 1)]; mx = fmaxf(mx, v); mn = fminf(mn, v); }
  mx = fmaxf(mx, __shfl_xor_sync(0xffffffffu, mx, 1));
  mn = fminf(mn, __shfl_xor_sync(0xffffffffu, mn, 1));
  const float mxs = mx * L2E, mns = mn * L2E;
#pragma unroll
  for (int i = 0; i < 10; i++) { const float v = p[4 * (i >> 1) + (i & 1)]; e[i] = fmaf(v, L2E, -mxs); e[10 + i] = fmaf(v, -L2E, mns); }
}
__device__ __forceinline__ void dual_norm(float* e, uint32_t* out) {
  float sp = 0.f, sn = 0.f;
#pragma unroll
  for (int i = 0; i < 10; i++) { e[i] = ex2(e[i]); e[10 + i] = ex2(e[10 + i]); sp += e[i]; sn += e[10 + i]; }
  sp += __shfl_xor_sync(0xffffffffu, sp, 1);
  sn += __shfl_xor_sync(0xffffffffu, sn, 1);
  sp = rcp(sp); sn = rcp(sn);
#pragma unroll
  for (int j = 0; j < 5; j++) { out[j] = pack(e[2 * j] * sp, e[2 * j + 1] * sp); out[5 + j] = pack(e[10 + 2 * j] * sn, e[11 + 2 * j] * sn); }
}

template <int K0, int CNT> __device__ __forceinline__ void conv_frags(uint32_t (*a)[4], uint32_t kt) {
#pragma unroll
  for (int i = 0; i < CNT; i++) {
    const uint32_t v2 = lds32(kt + (K0 - i) * 128), v1 = lds32(kt + (K0 - i) * 128 + 4), v0 = lds32(kt + (K0 - i) * 128 + 8);
    a[i][0] = __byte_perm(v0, v1, 0x5432); a[i][1] = v0; a[i][2] = __byte_perm(v1, v2, 0x5432); a[i][3] = v1;
  }
#pragma unroll
  for (int i = 0; i < CNT; i++) asm volatile("" : "+r"(a[i][0]), "+r"(a[i][2])::"memory");
}
template <int K0, int CNT> __device__ __forceinline__ void conv_mmas(float* acc, uint32_t (*a)[4], uint64_t ud) {
  constexpr int N = (128 - 4 * K0 + 7) / 8 * 8;
  WG<N>::template rs<0>(acc, a[0][0], a[0][1], a[0][2], a[0][3], ud + K0 * 4, 1);
  if constexpr (CNT > 1) conv_mmas<K0 - 1, CNT - 1>(acc, a + 1, ud);
}
template <int K0, int CNT> __device__ __forceinline__ void conv_issue(float* acc, uint32_t (*a)[4], uint64_t ud) {
  constexpr int R0 = K0 == 31 ? 0 : (128 - 4 * (K0 + 1) + 7) / 8 * 4, R1 = (128 - 4 * (K0 - CNT + 1) + 7) / 8 * 4;
#pragma unroll
  for (int i = R0; i < R1; i++) { acc[i] = 0.f; asm volatile("" : "+f"(acc[i])::"memory"); }
  wg_fence();
  conv_mmas<K0, CNT>(acc, a, ud);
  wg_commit();
}
template <int K0, int CNT> __device__ __forceinline__ void conv_batch(float* acc, uint32_t kt, uint64_t ud) {
  uint32_t a[CNT][4];
  conv_frags<K0, CNT>(a, kt);
  wg_wait<K0 < CW0 ? CW : 1>();
  conv_issue<K0, CNT>(acc, a, ud);
}

__device__ __forceinline__ void shift_add(uint32_t a, uint4* row, uint32_t e) {
  uint32_t y[2][4];
  uint4 v[4];
#pragma unroll
  for (int h = 0; h < 2; h++) {
#pragma unroll
    for (int l = 0; l < 4; l++) { if (h) lds128p(v[l], a + UPL + l * (US + 16), e); else v[l] = lds128(a + l * (US + 16)); }
    y[h][0] = hadd2(hadd2(v[0].x, v[1].x), hadd2(v[2].x, v[3].x)); y[h][1] = hadd2(hadd2(v[0].y, v[1].y), hadd2(v[2].y, v[3].y));
    y[h][2] = hadd2(hadd2(v[0].z, v[1].z), hadd2(v[2].z, v[3].z)); y[h][3] = hadd2(hadd2(v[0].w, v[1].w), hadd2(v[2].w, v[3].w));
  }
  y[0][0] = settag(y[0][0], e); y[0][2] = settag(y[0][2], e);
  stg128(row, __byte_perm(y[0][0], y[1][0], 0x5410), __byte_perm(y[0][0], y[1][0], 0x7632), __byte_perm(y[0][1], y[1][1], 0x5410), __byte_perm(y[0][1], y[1][1], 0x7632));
  stg128((uint4*)((uintptr_t)row ^ 16), __byte_perm(y[0][2], y[1][2], 0x5410), __byte_perm(y[0][2], y[1][2], 0x7632), __byte_perm(y[0][3], y[1][3], 0x5410), __byte_perm(y[0][3], y[1][3], 0x7632));
}

struct Params {
  const __nv_bfloat16 *prm[4], *wphi, *logdt, *Dsk, *gw;
  __nv_bfloat16* out;
  uint4* S;
};

__global__ void __launch_bounds__(512, 1)
fused_kernel(const __grid_constant__ CUtensorMap mx, const __grid_constant__ CUtensorMap mw, const __grid_constant__ CUtensorMap mwo, const __grid_constant__ Params P) {
  extern __shared__ __align__(1024) unsigned char smem_raw[];
  constexpr uint32_t sm = 1024, bars = sm + OFF_BAR;
  if ((uint32_t)__cvta_generic_to_shared(smem_raw) != sm) return;
  const int tid = threadIdx.x, lane = tid & 31;
  const int warp = __shfl_sync(0xffffffffu, tid >> 5, 0);
  const int bid = blockIdx.x, r = bid >> 4, c = bid & 15;
  unsigned* const cnt = (unsigned*)P.S;
  int budget = 1 << 24;

  if (tid == 0) {
    mbar_init(bars + B_FULL, 1);
    asm volatile("fence.mbarrier_init.release.cluster;" ::: "memory");
    mbar_expect(bars + B_FULL, XB + W_TX);
    asm volatile("prefetch.tensormap [%0];" ::"l"(&mx) : "memory");
    tma3(sm + XB, &mw, (40 * c) & ~15, 0, 0, bars + B_FULL);
    tma2(sm, &mx, 0, r * 256, bars + B_FULL);
    TS(26);
  }
  __syncwarp();
  if (warp >= 12) {
    asm volatile("setmaxnreg.dec.sync.aligned.u32 32;");
    if (warp == 12) {
      if (lane == 0) {
        mbar_init(bars + B_FULL + 8, 1); mbar_init(bars + B_FULL + 16, 1);
        asm volatile("fence.mbarrier_init.release.cluster;" ::: "memory");
      }
      __syncwarp();
      bar_arrive(0, 384);
      int s = 1, ph = 1;
#pragma unroll 1
      for (int kb = 1; kb < 10; kb++) {
        const uint32_t fb = bars + B_FULL + 8 * s;
        if (kb == 3) bar_sync(8, 64);
        if (lane == 0) {
          if (kb >= 3) mbar_wait(fb + B_EMPTY, ph);
          mbar_expect(fb, XB + W_TX);
          tma3(sm + s * STG + XB, &mw, (40 * c) & ~15, kb * 64, 0, fb);
          tma2(sm + s * STG, &mx, kb * 64, r * 256, fb);
        }
        __syncwarp();
        if (++s == 3) { s = 0; ph ^= 1; }
      }
      if (lane == 0) {
        mbar_wait(bars + B_EMPTY + 8, 0);
        mbar_wait(bars + B_EMPTY + 16, 0);
        mbar_wait(bars + B_U + 8, 0);
#pragma unroll 1
        for (int i = WO0; i < 5; i++) {
          const uint32_t wb = i < 4 ? bars + B_W2 : bars + B_WO;
          mbar_expect(wb, 20480);
          tma5(sm + OFF_WO + i * 20480, &mwo, 80 * (c & 7) + 16 * i, wb);
          mbar_wait(wb, i & 1);
        }
        TS(29);
      }
    } else {
      if (tid == 416) {
#pragma unroll
        for (int o = B_EMPTY; o < O_EPOCH; o += 8)
          mbar_init(bars + o, o < B_WO ? 3 : (o == B_KG || o == B_BT) ? 128 : o == B_P1 ? 2 : o == B_CD ? 20 : ((o >= B_UE && o <= B_CD) || o == B_KVD) ? 4 : 1);
        asm volatile("fence.mbarrier_init.release.cluster;" ::: "memory");
      }
      __syncwarp();
      if (lane == 0) TS(23 + warp);
      if (warp == 13) { bar_arrive(7, 160); bar_arrive(8, 64); }
      bar_sync(0, 384);
      if (warp == 13) {
        const int cj = c & 7, th = c >> 3;
        const int q = (lane & 7) >> 1, tok = 128 * th + 16 * (3 - q) + 4 * ((lane >> 3) ^ (q & 1)) + (q & 2) + (lane & 1);
        const uint32_t a0 = sm + tok * 128 + ((cj ^ (tok & 7)) << 4), a1 = a0 ^ 0x120;
        uint4* d = P.S + S_U + (8 * cj + (lane >> 2)) * 256 + (124 - 16 * r - 8 * th + (lane & 3) + (lane & 2) * 64);
        const bool sw = lane & 1;
        int s = 0, ph = 0;
#pragma unroll 1
        for (int kb = 0; kb < 10; kb++) {
          mbar_wait(bars + B_FULL + 8 * s, ph);
          uint32_t v[4][4];
          const uint32_t xs = s * STG;
          ldsm4t(v[0], xs + a0); ldsm4t(v[1], xs + a0 + 8192); ldsm4t(v[2], xs + a1); ldsm4t(v[3], xs + a1 + 8192);
#pragma unroll
          for (int i = 0; i < 4; i++)
            stg128((uint4*)((uintptr_t)d ^ (i >> 1) * 2048) - (i & 1) * 4, sw ? v[i][1] : v[i][0], sw ? v[i][0] : v[i][1], sw ? v[i][3] : v[i][2], sw ? v[i][2] : v[i][3]);
          d += 64 * 256;
          __syncwarp();
          if (lane == 0) { mbar_arrive(bars + B_EMPTY + 8 * s); if (kb & 1) mbar_arrive(bars + B_XW + 4 * (kb - 1)); }
          if (++s == 3) { s = 0; ph ^= 1; }
        }
      } else if (lane == 0) {
        if (warp == 14) {
#pragma unroll 1
          for (int ci = 0; ci < 5; ci++) { mbar_wait(bars + B_XW + 8 * ci, 0); cnt_release(cnt + ci * 32 + 4); }
        } else {
          const unsigned ep = (atomicAdd(cnt + c * 32, 1u) >> 3) + 1;
          sts32(bars + O_EPOCH, ep);
          mbar_arrive(bars + B_EP);
          const uint4* src = P.S + S_U + bid * 256;
#pragma unroll 1
          for (int ci = 0; ci < 5; ci++) {
            cnt_wait(cnt + ci * 32 + 4, 128u * ep);
            fence_async_all();
            mbar_wait(ci >= 2 ? bars + B_UE + 8 * (ci & 1) : bars + B_KU, ci >> 2);
            const uint32_t ub = bars + B_U + 8 * (ci & 1), dst = sm + OFF_U + (ci & 1) * US;
            mbar_expect(ub, 4096);
            bulk(dst, src, 2048, ub);
            bulk(dst + UPL, src + 128, 2048, ub);
            src += 128 * 256;
          }
        }
      }
      __syncwarp();
      if (warp < 15) {
        const int n = 127 - (warp - 13) * 64 - lane;
        uint4* row = P.S + S_B + ((n >> 3) * 640 + bid) * 16 + ((2 * (n & 7)) ^ (bid & 7));
        uint32_t a = sm + OFF_P + (127 - n) * 16;
        mbar_wait(bars + B_EP, 0);
        uint32_t it = lds32(bars + O_EPOCH) & 1u;
#pragma unroll 1
        do {
          if (!(it & 64)) bar_sync(9, 192);
          shift_add(a, row, it);
          row += (it & 64) ? 4 * 640 * 16 + 128 * 16 : -4 * 640 * 16;
          a ^= 512;
          if (it & 64) {
            bar_arrive(10, 192);
            if (tid == 416) TS(18 + (it >> 7));
          }
          it += 64;
          pin(it);
        } while (it < 512);
      }
    }
  } else if (warp >= 8) {
    const int t = tid - 256, w = warp - 8, g = lane >> 2, tq = lane & 3;
    {
      const __nv_bfloat16* src = P.prm[(t >> 4) & 3] + (bid + (t >> 6) * 128) * 128 + (t & 15) * 8;
#pragma unroll
      for (int i = 0; i < 3; i++)
        if (i < 2 || t < 64) asm volatile("cp.async.cg.shared.global [%0], [%1], 16;" ::"r"(sm + OFF_PRM + t * 16 + i * 2048), "l"(src + i * 32768) : "memory");
    }
    uint32_t dtr = ldu16(P.logdt + bid + 128 * min(lane, 4)), dsr = ldu16(P.Dsk + bid + 128 * min(lane, 4));
    if (t == 0) TS(14);
    {
      constexpr float L2E = 1.4426950408889634f;
      uint32_t aA = sm + OFF_KA + ((t >> 3) & 7) * 2048 + (w >> 1) * 1024 + (lane & 7) * 16;
      uint32_t aB = sm + OFF_KA + 16384 + ((t >> 3) & 7) * 1536 + (w >> 1) * 768 + (lane & 7) * 16;
      const int i0 = 16 * (w & 1) + g;
      constexpr int TG = 2768;
      const uint32_t T = sm + OFF_KT, Ts = T + (w >> 1) * TG;
      uint32_t p0 = Ts + (8 * i0 + (2 * tq ^ (g >> 2) * 2)) * 4, p1 = Ts + (256 + 8 * i0 + (2 * tq ^ (g >> 2) * 4)) * 4, p1h = (p1 ^ 8) + 256, p2 = Ts + (512 + 72 * tq + i0) * 4;
      auto at1 = [&](int row, int col) { return T + (256 + 8 * row + (col ^ (row & 4) ^ ((row & 8) >> 2))) * 4; };
      auto ix3 = [&](int i) { return T + (512 + 36 * (i >> 5) + (i & 31)) * 4; };
      auto ix2 = [&](int i) { return at1((i >> 1) & 31, 4 + 2 * (i >> 6) + (i & 1)); };
      uint32_t ea[7] = {T + (8 * (t >> 2) + ((4 * (t & 1) + ((t >> 1) & 1)) ^ ((t >> 3) & 2))) * 4, at1(t >> 2, 2 * (t & 1) + ((t >> 1) & 1)),
                        t == 127 ? ix2(0) : at1((t + 1) >> 2, ((t + 1) >> 1) & 1), ix2(t), t == 127 ? ix3(0) : ix2(t + 1), ix3(t), ix3(t + 1)};
#pragma unroll
      for (int i = 0; i < 7; i++) pin(ea[i]);
      pin(aA); pin(aB); pin(p0); pin(p1); pin(p1h); pin(p2);
      float dtv = 0.f, d[24];
#pragma unroll
      for (int i = 0; i < 24; i++) d[i] = 0.f;
#pragma unroll 1
      for (int p = -1;; p++) {
        uint32_t gr[4], gi[4], qr[4], qi[4], yr, yi, m[8];
        if (p < 5) {
          const uint32_t pr = sm + OFF_PRM + t * 2 + p * 1024;
          const float dt = __shfl_sync(0xffffffffu, dtv, p);
          const float lr = bfr(ex2(bf_lo(lds16(pr)) * L2E)) * (dt * -L2E), li = bf_lo(lds16(pr + 256)) * dt;
          const cplx v0 = {bf_lo(lds16(pr + 512)) * (2.f * dt), bf_lo(lds16(pr + 768)) * (-2.f * dt)};
          const cplx w1 = cexp2(lr, -li), Z = cexp2(256.f * lr, -256.f * li), w2 = csq(w1), w4 = csq(w2), v4 = cmul(v0, w4);
          const cplx G1 = {w4.r * w4.r - w4.i * w4.i, -2.f * w4.r * w4.i}, G2 = csq(G1), G3 = cmul(G2, G1), G4 = csq(G2), W1 = csq(G4), W2 = csq(W1), W3 = cmul(W2, W1);
          const cplx Z2 = csq(Z), y4 = cmul(v0, csq(Z2)), y5 = cmul(y4, Z);
          gr[0] = pack(1.f, G1.r); gi[0] = pack(0.f, G1.i); gr[1] = pack(G2.r, G3.r); gi[1] = pack(G2.i, G3.i);
          qr[0] = pack(v0.r, v4.r); qi[0] = pack(v0.i, v4.i); yr = pack(y4.r, y5.r); yi = pack(y4.i, y5.i);
          m[0] = pack(G4.r, G4.i); m[1] = pack(W1.r, W1.i); m[2] = pack(W2.r, W2.i); m[3] = pack(W3.r, W3.i);
          m[4] = pack(w1.r, w1.i); m[5] = pack(w2.r, w2.i); m[6] = pack(Z.r, Z.i); m[7] = pack(Z2.r, Z2.i);
        }
        if (p < 0) {
          if (t == 0) TS(30);
          if (t == 64) TS(31);
#pragma unroll
          for (int i = 0; i < 8; i++) pin(m[i]);
          pin(gr[0]); pin(gi[0]); pin(gr[1]); pin(gi[1]); pin(qr[0]); pin(qi[0]); pin(yr); pin(yi);
          pin(dtr); pin(dsr);
          dtv = __shfl_sync(0xffffffffu, bf_lo(dsr), lane & 7);
          if (lane < 8) dtv = bfr(ex2(bf_lo(dtr) * L2E));
          asm volatile("cp.async.wait_all;" ::: "memory");
          if (t == 0) TS(32);
          bar_sync(4, 128);
          if (t == 0) TS(13);
          continue;
        }
        wg_wait<0>();
        fence_regs<24>(d);
        if (p != 0) {
          auto part = [&](const float* q) {
            sts64f(p0, q[0], q[1]); sts64f(p0 + 256, q[2], q[3]); sts64f(p1, q[4], q[5]); sts64f(p1h, q[6], q[7]);
            if (tq < 3) { stsf(p2, q[8]); stsf(p2 + 32, q[10]); }
            if (tq < 2) { stsf(p2 + 144, q[9]); stsf(p2 + 176, q[11]); }
          };
          if (w < 2) part(d); else part(d + 12);
        }
        if (p == 1) bar_sync(7, 160); else bar_sync(4, 128);
        if (t == 0 && p < 2) TS(34 + p);
        float tv[16];
#pragma unroll
        for (int i = 0; i < 16; i++) tv[i] = __uint_as_float(lds32((i < 2 ? ea[0] : i < 4 ? ea[0] ^ 8 : ea[(i >> 1) - 1]) + (i & 1) * TG));
        float ds = __shfl_sync(0xffffffffu, dtv, p + 7);
        ds = t == 0 ? ds : 0.f;
        if (p < 5) {
          uint32_t re[4], im[4];
          hcmul(gr[2], gi[2], gr[0], gi[0], m[0]); hcmul(gr[3], gi[3], gr[1], gi[1], m[0]);
          sts128(aA, make_uint4(gr[0], gr[1], gr[2], gr[3])); sts128(aA + 128, make_uint4(gi[0], gi[1], gi[2], gi[3]));
#pragma unroll
          for (int j = 1; j < 4; j++) {
#pragma unroll
            for (int i = 0; i < 4; i++) hcmul(re[i], im[i], gr[i], gi[i], m[j]);
            sts128(aA + j * 256, make_uint4(re[0], re[1], re[2], re[3])); sts128(aA + j * 256 + 128, make_uint4(im[0], im[1], im[2], im[3]));
          }
          hcmul(qr[1], qi[1], qr[0], qi[0], m[4]); hcmul(qr[2], qi[2], qr[0], qi[0], m[5]); hcmul(qr[3], qi[3], qr[2], qi[2], m[4]);
          sts128(aB, make_uint4(qr[0], qr[1], qr[2], qr[3])); sts128(aB + 128, make_uint4(qi[0], qi[1], qi[2], qi[3]));
          hcmul(re[0], im[0], qr[0], qi[0], m[6]); hcmul(re[1], im[1], qr[2], qi[2], m[6]);
          hcmul(re[2], im[2], qr[0], qi[0], m[7]); hcmul(re[3], im[3], re[0], im[0], m[7]);
          sts128(aB + 256, make_uint4(re[0], re[1], re[2], re[3])); sts128(aB + 384, make_uint4(im[0], im[1], im[2], im[3]));
          hcmul(re[1], im[1], yr, yi, m[7]); hcmul(re[2], im[2], re[1], im[1], m[7]);
          sts128x(aB + 512, yr, re[1], re[2]); sts128x(aB + 640, yi, im[1], im[2]);
        } else if (t == 0) mbar_arrive(bars + B_KU);
        const float k0 = tv[0] + tv[1] + ds, X2 = tv[8] + tv[9], Y2 = tv[10] + tv[11], X3 = tv[12] + tv[13], Y3 = tv[14] + tv[15];
        uint32_t tw[7] = {pack(tv[2] + tv[3], k0), pack(tv[6] + tv[7], tv[4] + tv[5]), pack(X2, X2), pack(Y2, (t & 1) ? Y2 : X2), pack(X3, X3), pack(Y3, (t & 1) ? Y3 : X3), pack(Y3, Y3)};
#pragma unroll
        for (int i = 0; i < 7; i++) pin(tw[i]);
        const uint32_t kw = sm + OFF_KTAB + 32 + max(p - 1, 0) * KTS;
        if (p == 5) {
          if (t < 8) sts32(kw - 32 + t * 4, 0);
          sts32(kw + t * 4, tw[0]); sts32(kw + 512 + t * 4, tw[1]); sts64(kw + 1024 + t * 8, tw[2], tw[3]); sts128(kw + 2048 + t * 16, make_uint4(tw[4], tw[4], tw[5], tw[6]));
          break;
        }
        fence_async_smem();
        bar_sync(4, 128);
        const uint64_t ad = mkdesc(sm + OFF_KA, 128, 256, 0) + (p >> 8);
        wg_fence();
#pragma unroll
        for (int k = 0; k < 8; k++) {
          WG<48>::ss<1, 1>(d, ad + k * 128, ad + 1024 + k * 96, k != 0);
          if (k == 1) { if (t < 8) sts32(kw - 32 + t * 4, 0); sts32(kw + t * 4, tw[0]); sts32(kw + 512 + t * 4, tw[1]); }
          if (k == 3) sts64(kw + 1024 + t * 8, tw[2], tw[3]);
          if (k == 5) sts128(kw + 2048 + t * 16, make_uint4(tw[4], tw[4], tw[5], tw[6]));
        }
        wg_commit();
      }
    }
    if (t == 0) TS(15);
#pragma unroll
    for (int i = 0; i < 4; i++) sts128(sm + OFF_B2 + (t + 128 * i) * 16, make_uint4(0, 0, 0, 0));
    bar_sync(4, 128);
    if (t < 48) sts128(sm + (t < 16 ? OFF_U : OFF_P - 4 * UPL) + (t >> 2) * UPL + 2048 + (t & 3) * 16, make_uint4(0, 0, 0, 0));
    fence_async_smem();
    mbar_arrive(bars + B_KG);
    bar_sync(4, 128);
    if (t == 0) TS(16);
    const uint32_t pa = sm + OFF_P + w * US + ((lane >> 3) & 1) * UPL + ((lane & 7) + ((lane >> 4) << 3)) * 16;
    uint32_t kt = sm + OFF_KTAB + (6 + 8 * w + g - 2 * tq) * 4;
    float acc[64];
#pragma unroll
    for (int i = 0; i < 64; i++) asm volatile("" : "=f"(acc[i]));
#pragma unroll 1
    for (int ci = 0;; ci++) {
      const uint64_t ud = mkdesc(sm + OFF_U, UPL, 128, 0) + (ci & 1) * (US / 16);
      uint32_t a0[CB0][4];
      conv_frags<31, CB0>(a0, kt);
      if (ci == EARLY) { mbar_wait(bars + B_P1, 0); if (t == 0) TS(17); }
      if (ci < 5) mbar_wait(bars + B_U + 8 * (ci & 1), (ci >> 1) & 1);
      if (t == 0) TS(40 + 4 * ci);
      if (ci >= 2) bar_sync(10, 192);
      wg_wait<0>();
      fence_regs<64>(acc);
      if (t == 0) TS(41 + 4 * ci);
      uint32_t pp[32];
#pragma unroll
      for (int i = 0; i < 32; i++) { pp[i] = pack(acc[2 * i], acc[2 * i + 1]); asm volatile("" : "+r"(pp[i])::"memory"); }
      conv_issue<31, CB0>(acc, a0, ud);
      if (ci > 0) {
        if (lane == 0) mbar_arrive(bars + B_UE + 8 * (~ci & 1));
#pragma unroll
        for (int j = 0; j < 8; j++) stsm4t(pa + j * 256, pp[4 * j], pp[4 * j + 1], pp[4 * j + 2], pp[4 * j + 3]);
        if (ci == 5) break;
        bar_arrive(9, 192);
      }
      if (t == 0) TS(42 + 4 * ci);
      conv_batch<27, 5>(acc, kt, ud); conv_batch<22, 5>(acc, kt, ud); conv_batch<17, 4>(acc, kt, ud); conv_batch<13, 3>(acc, kt, ud); conv_batch<10, 3>(acc, kt, ud);
      if (SIG == 1 && lane == 0) mbar_arrive(bars + B_CD);
      conv_batch<7, 2>(acc, kt, ud); conv_batch<5, 2>(acc, kt, ud);
      if (SIG == 2 && lane == 0) mbar_arrive(bars + B_CD);
      conv_batch<3, 2>(acc, kt, ud); conv_batch<1, 2>(acc, kt, ud);
      if (SIG == 3 && lane == 0) mbar_arrive(bars + B_CD);
      if (t == 0) TS(43 + 4 * ci);
      kt += KTS;
    }
    wg_wait<0>();
    {
      const unsigned ep = lds32(bars + O_EPOCH);
      const uint4* src = P.S + S_B + ((2 * r + (c >> 3)) * 8 + (c & 7)) * 1280 + t;
      const int n = 127 - t;
      uint4* row = P.S + S_B + ((n >> 3) * 640 + bid + 512) * 16 + ((2 * (n & 7)) ^ (bid & 7));
      pin(src); pin(row);
      bar_sync(4, 128);
      shift_add(sm + OFF_P + t * 16, row, ep & 1u);
      if (t == 0) TS(22);
      uint4 v[10];
      uint32_t bad;
#pragma unroll
      for (int i = 0; i < 10; i++) undef(v[i], ep);
      do {
#pragma unroll
        for (int i = 0; i < 10; i++) ldg128t(v[i], src + i * 128, ep);
        bad = or3(or3(tag2(v[0].x, v[1].x, ep), tag2(v[2].x, v[3].x, ep), tag2(v[4].x, v[5].x, ep)), tag2(v[6].x, v[7].x, ep), tag2(v[8].x, v[9].x, ep));
        budget -= 16;
      } while ((bad & 1u) && budget > 0);
#pragma unroll
      for (int i = 0; i < 10; i++) sts128(sm + OFF_KTAB + t * 16 + i * 2048, v[i]);
      mbar_arrive(bars + B_BT);
      if (t == 0) TS(23);
    }
  } else {
    constexpr float L2E = 1.4426950408889634f;
    const int wg = warp >> 2, w = warp & 3, g = lane >> 2, tq = lane & 3, t = tid & 127;
    uint32_t gk[2];
    {
      uint32_t gv[4];
#pragma unroll
      for (int i = 0; i < 4; i++) gv[i] = ldu16(P.gw + (i < 3 ? min(tid, 191) : tid & 63) + 192 * i);
      const int ng = tid / 48, k = tid - ng * 48;
      uint32_t w0 = 0, w1 = 0;
      if (tid < 240 && k < 40) {
        const uint32_t* src = (const uint32_t*)(P.wphi) + (c * 400 + k * 10 + ng);
        w0 = __ldg(src); w1 = __ldg(src + 5);
      }
      const uint32_t ga = sm + XB + (tid >> 6) * STG + (tid & 63) * 128 + ((~tid & 7) << 4);
      if (tid < 240) sts128(sm + OFF_WPHI + tid * 16, make_uint4(k < 20 ? w0 : 0, k < 20 ? w1 : 0, k < 20 ? 0 : w0, k < 20 ? 0 : w1));
#pragma unroll
      for (int i = 0; i < 4; i++)
        if (tid < (i < 3 ? 192 : 64)) asm volatile("st.shared.u16 [%0], %1;" ::"r"((ga ^ (i & 1) * 16) + i * 4096), "h"((unsigned short)gv[i]) : "memory");
#pragma unroll
      for (int h = 0; h < 2; h++) {
        const int hi = t >= 84, j = hi ? 1 : 2 * h, rt = hi ? min(t - 84, 41) + 42 * h : t, m = rt >> 1, md = m / 10;
        gk[h] = ((j * 88 + rt) << 16) + j * 512 + (rt < 80 ? ((m - 10 * md) >> 1) * 1280 + (2 * md + (m & 1)) * 16 + (md & 2) * 4 : 6400 + (m & 1) * 72) + (rt & 1) * 4;
        pin(gk[h]);
      }
      if (lane < 3) mbar_init(bars + 256 + warp * 32 + lane * 8, 1);
      if (tid == 0) TS(24);
      if (tid == 224) TS(39);
      if (tid == 96) TS(33);
      bar_sync(0, 384);
      asm volatile("setmaxnreg.inc.sync.aligned.u32 176;");
      if (tid == 0) TS(25);
    }
    uint32_t va[64];
    {
      float acc[128];
#pragma unroll
      for (int i = 0; i < 128; i++) acc[i] = 0.f;
      const int isB = (lane >> 3) & 1;
      const int sec = warp < 5 ? 1 - isB : 2, chk = warp < 5 ? warp : (warp - 5) * 2 + isB;
      const bool gate = chk == 5;
      uint32_t aa = sm + XB + (gate ? 0 : sec * 8192) + ((lane >> 4) * 8 + (lane & 7)) * 128 + (((gate ? 7 : chk + (c & 1)) ^ (lane & 7)) << 4);
      const uint32_t gx = gate ? 16 : 0;
      uint32_t a[2][4];
      mbar_wait(bars + B_FULL, 0);
      if (tid == 0) TS(0);
      ldsm4t(a[0], aa);
#pragma unroll 1
      for (int rd = 0;; rd++) {
        const uint64_t bd = mkdesc(sm, 16, 1024, 1) + (rd >> 8);
#pragma unroll
        for (int s = 0; s < 3; s++) {
#pragma unroll
          for (int k = 0; k < 4; k++) {
            const uint32_t* q = a[k & 1];
            wg_fence();
            WG<128>::rs<0>(acc, q[0], q[1], q[2], q[3], bd + s * (STG / 16) + 2 * k, 1);
            WG<128>::rs<0>(acc + 64, q[0], q[1], q[2], q[3], bd + s * (STG / 16) + 1024 + 2 * k, 1);
            wg_commit();
            if (k == 3) {
              if (s == 2) aa = (aa + gx * 256) ^ gx;
              mbar_wait(bars + B_FULL + 8 * ((s + 1) % 3), s == 2 ? ~rd & 1 : s == 0 ? rd == 1 : rd & 1);
            }
            ldsm4t(a[~k & 1], aa + (k == 3 ? (s + 1) % 3 * STG : s * STG + (k + 1) * 2048));
            wg_wait<0>();
          }
          if (t == 0) mbar_arrive(bars + B_EMPTY + 8 * s);
          if (s == 0 && rd == 3) goto p1_done;
        }
      }
    p1_done:
      fence_regs<128>(acc);
      if (P1POS == 0 && t == 0) mbar_arrive(bars + B_P1);
      if (tid == 0) TS(1);
#pragma unroll
      for (int i = 32; i < 64; i++) { va[i] = pack(acc[2 * i], acc[2 * i + 1]); pin(va[i]); }
      mbar_wait(bars + B_EMPTY, 1);
      fence_regs<64>(acc);
#pragma unroll
      for (int i = 0; i < 32; i++) va[i] = pack(acc[2 * i], acc[2 * i + 1]);
    }
    {
      const uint32_t ka = sm + min(warp, 5) * 1024 + ((lane >> 3) & 1) * 10240 + (lane >> 4) * 128 + (lane & 7) * 16;
      if (warp < 5 || warp == 7) {
#pragma unroll
        for (int S = 0; S < 16; S++) stsm4t(ka + (S >> 2) * MBS + (S & 3) * 256, va[4 * S], va[4 * S + 1], va[4 * S + 2], va[4 * S + 3]);
      }
      if (warp == 7) {
#pragma unroll
        for (int i = 0; i < 32; i++) va[2 * i + 1] = 0x3F803F80u;
      }
    }
    fence_async_smem();
    mbar_wait(bars + B_EP, 0);
    const unsigned ep = lds32(bars + O_EPOCH);
    bar_sync(1, 256);
    if (tid == 0) TS(2);
    const uint32_t mb0 = sm + 2 * wg * MBS;
    {
      const uint32_t sta = mb0 + (2 * w + ((lane >> 3) & 1)) * 128 + (lane & 7) * 16 + (lane >> 4) * 1024;
      float pn[20];
      auto feat = [&](int j) {
        const uint64_t wd = mkdesc(sm + OFF_WPHI, 128, 768, 0), ad = mkdesc(sm, 1024, 128, 0) + ((2 * wg + (j & 1)) * MBS + (j >> 1) * 10240) / 16;
        wg_fence();
        WG<40>::ss<0, 1>(pn, ad, wd, 0);
        WG<40>::ss<0, 1>(pn, ad + 128, wd + 16, 1);
        WG<40>::ss<0, 1>(pn, ad + 256 - (64ull << 16), wd + 32, 1);
        wg_commit();
      };
      feat(0);
#pragma unroll 1
      for (int j = 0; j < 4; j++) {
        float e[40];
        wg_wait<0>();
        fence_regs<20>(pn);
        dual_exp(pn, e);
        dual_exp(pn + 2, e + 20);
        fence_regs<40>(e);
        feat(j + 1);
        uint32_t f0[10], f1[10];
        dual_norm(e, f0);
        dual_norm(e + 20, f1);
        if (j == 2) mbar_wait(bars + B_KVD, 0);
#pragma unroll
        for (int i = 0; i < 5; i++) stsm4(sta + (j & 1) * MBS + i * 2048, f0[2 * i], f1[2 * i], f0[2 * i + 1], f1[2 * i + 1]);
        if (P1POS >= 1 && P1POS - 1 == j && t == 0) mbar_arrive(bars + B_P1);
        if (j == 1) {
          fence_async_smem();
          if (tid == 0) TS(3);
          if (wg == 0) bar_arrive(2, 256);
          else {
            bar_sync(2, 256);
            float kv[40];
            const uint64_t bd = mkdesc(sm, 128, 1024, 0) + blockIdx.y;
            wg_fence();
#pragma unroll
            for (int S = 0; S < 16; S++) WG<80>::rs<1>(kv, va[4 * S], va[4 * S + 1], va[4 * S + 2], va[4 * S + 3], bd + ((S >> 2) * MBS + (S & 3) * 256) / 16, S != 0);
            wg_commit();
            uint4* dst[2];
#pragma unroll
            for (int h = 0; h < 2; h++) {
              const int m = 16 * (w - 1) + 8 * h + g;
              dst[h] = P.S + S_KV + (c * 8 + r) * 264 + (m == 40 ? 80 + tq : (unsigned)(m - 10 * (tq & 2)) < 20u ? 2 * m + (tq & 1) : 84);
              pin(dst[h]);
            }
            wg_wait<0>();
            fence_regs<40>(kv);
            if (lane == 0) mbar_arrive(bars + B_KVD);
#pragma unroll
            for (int h = 0; h < 2; h++) {
              uint32_t x[10];
#pragma unroll
              for (int i = 0; i < 10; i++) x[i] = pack(kv[4 * i + 2 * h], kv[4 * i + 2 * h + 1]);
              stg128(dst[h], settag(x[0], ep), x[1], x[2], x[3]);
              stg128(dst[h] + 88, settag(x[4], ep), x[5], x[6], x[7]);
              stg128(dst[h] + 176, settag(x[8], ep), x[9], __float_as_uint(kv[0]), __float_as_uint(kv[1]));
            }
            if (t == 0) TS(4);
          }
        }
      }
      wg_wait<0>();
      fence_regs<20>(pn);
    }
    if (tid == 0) TS(5);
    uint32_t hh[2];
    {
      const uint32_t ga = sm + (2 * (c >> 3) + wg) * MBS + 15360 + (16 * w + g) * 16;
      hh[0] = lds16(ga); hh[1] = lds16(ga + 128);
    }
    if (wg == 0) {
      const int hi = t >= 84;
      uint32_t ad[2];
      const uint4* src[2];
#pragma unroll
      for (int h = 0; h < 2; h++) { ad[h] = sm + OFF_B2 + (gk[h] & 0xFFFF); src[h] = P.S + S_KV + c * 8 * 264 + (gk[h] >> 16); }
      uint4 v[2][8];
      uint32_t bad;
#pragma unroll
      for (int i = 0; i < 16; i++) undef(v[i >> 3][i & 7], ep);
      do {
#pragma unroll
        for (int i = 0; i < 16; i++) ldg128t(v[i >> 3][i & 7], src[i >> 3] + (i & 7) * 264, ep);
        bad = 0;
#pragma unroll
        for (int i = 0; i < 4; i++) bad = or3(bad, tag2(v[0][2 * i].x, v[0][2 * i + 1].x, ep), tag2(v[1][2 * i].x, v[1][2 * i + 1].x, ep));
        budget -= 16;
      } while ((bad & 1u) && budget > 0);
      if (tid == 0) TS(6);
      mbar_wait(bars + B_KG, 0);
#pragma unroll
      for (int h = 0; h < 2; h++) {
        uint4* u = v[h];
#pragma unroll
        for (int st = 4; st > 0; st >>= 1)
#pragma unroll
          for (int i = 0; i < st; i++) { u[i].x = hadd2(u[i].x, u[i + st].x); u[i].y = hadd2(u[i].y, u[i + st].y); u[i].z = hadd2(u[i].z, u[i + st].z); u[i].w = hadd2(u[i].w, u[i + st].w); }
        const uint32_t a1 = ad[h], a2 = a1 >= sm + OFF_B2 + 6400 ? a1 + 32 : a1;
        sts32(a1, u[0].x); sts32(a1 + 128, u[0].y); sts32(a2, u[0].x); sts32(a2 + 128, u[0].y);
        if (h == 0 || hi) { sts32(a1 + 256, u[0].z); sts32(a1 + 384, u[0].w); sts32(a2 + 256, u[0].z); sts32(a2 + 384, u[0].w); }
      }
    }
    fence_async_smem();
    bar_sync(1, 256);
    if (tid == 0) TS(7);
    {
      float oa[2][24];
      const uint64_t bd = mkdesc(sm + OFF_B2, 128, 1280, 0) + blockIdx.y, ad = mkdesc(sm, 1024, 128, 0) + wg * (2 * MBS / 16);
      wg_fence();
#pragma unroll
      for (int s = 0; s < 10; s++) WG<48>::ss<0, 0>(oa[s / 5], ad + (s % 5) * 128 + (s / 5) * (MBS / 16), bd + (s % 5) * 16, s % 5 != 0);
      wg_commit();
      uint4* od = P.S + S_O + ((4 * r + 2 * wg) * 8 + (c >> 1)) * 640 + w * 160 + (c & 1) * 64 + lane;
      uint2* od8 = (uint2*)(P.S + S_O + ((4 * r + 2 * wg) * 8 + (c >> 1)) * 640 + w * 160 + 128 + lane) + (c & 1);
      unsigned* oc = cnt + (2 * r + wg) * 32 + 2 + (lane & 1);
      float ge[4];
#pragma unroll
      for (int i = 0; i < 4; i++) ge[i] = 1.f + ex2(-L2E * bf_lo(lds16(mb0 + 15360 + (16 * w + g) * 16 + (i >> 1) * MBS + (i & 1) * 128)));
      const float h0 = rcp(1.f + ex2(L2E * bf_lo(hh[0]))), h1 = rcp(1.f + ex2(L2E * bf_lo(hh[1])));
      hh[0] = pack(h0, h0); hh[1] = pack(h1, h1);
      fence_regs<4>(ge);
      pin(hh[0]); pin(hh[1]); pin(od); pin(od8); pin(oc);
      wg_wait<0>();
      fence_regs<48>(&oa[0][0]);
      if (tid == 0) TS(27);
#pragma unroll
      for (int i = 0; i < 2; i++) {
        const float r0 = rcp(ge[2 * i] * (oa[i][20] + 1e-6f)), r1 = rcp(ge[2 * i + 1] * (oa[i][22] + 1e-6f));
        uint32_t o0[5], o1[5];
#pragma unroll
        for (int j = 0; j < 5; j++) { o0[j] = pack(oa[i][4 * j] * r0, oa[i][4 * j + 1] * r0); o1[j] = pack(oa[i][4 * j + 2] * r1, oa[i][4 * j + 3] * r1); }
        stg128(od + i * 8 * 640, settag(o0[0], ep), o1[0], o0[1], o1[1]);
        stg128(od + i * 8 * 640 + 32, settag(o0[2], ep), o1[2], o0[3], o1[3]);
        stg64(od8 + i * 16 * 640, settag(o0[4], ep), o1[4]);
      }
      if (lane < 2) asm volatile("red.relaxed.gpu.global.add.u32 [%0], 1;" ::"l"(oc) : "memory");
    }
    if (tid == 0) TS(8);
    const int ft = 2 * r + (c >> 3);
    uint32_t ba, oa, orr;
    __nv_bfloat16* og;
    const uint32_t ob = mb0 + w * 8192;
    {
      const int chl = (lane & 7) + ((lane >> 4) << 3), tg = 8 * wg + 2 * w + ((lane >> 3) & 1);
      ba = sm + OFF_KTAB + chl * 256 + ((tg ^ (lane & 7)) << 4);
      oa = ob + (lane & 15) * 176 + (lane >> 4) * 16;
      orr = ob + (lane & 15) * 176;
      og = P.out + (128 * ft + 64 * wg + 16 * w + (lane & 15)) * 640 + 80 * (c & 7);
      pin(ba); pin(oa); pin(orr); pin(og);
    }
    float acc[40];
    uint32_t bt[20];
    {
      uint4 A[2][5];
      const uint4* src = P.S + S_O + (2 * ft + wg) * 8 * 640 + w * 160;
      uint32_t rb = bars + 256 + warp * 32, ra = ob + lane * 16;
      pin(src); pin(rb); pin(ra);
      auto fill = [&](int p, uint32_t z) { if (lane == 0) { mbar_expect(rb + (p % 3) * 8, 2560 | z); bulk(ob + (p % 3) * 2560, src + p * 640, 2560, rb + (p % 3) * 8); } };
      if (tid == 0) TS(28);
      mbar_wait(bars + B_WO, 0);
      if (w == 0) cnt_poll(cnt + ft * 32 + 2 + wg, 64u * ep);
      bar_sync(5 + wg, 128);
      if (tid == 0) TS(9);
      const uint64_t bd = mkdesc(sm + OFF_WO, 20480, 256, 3);
#pragma unroll 1
      for (int redo = 0; redo < 1000; redo++) {
        fill(0, 0); fill(1, 0); fill(2, 0);
        if (DLY == 2) mbar_wait(bars + B_CD, 0);
        uint32_t bad = 0;
#pragma unroll
        for (int p = 0; p < 8; p++) {
          uint4* a = A[p & 1];
          mbar_wait(rb + (p % 3) * 8, (p % 3 == 2 ? 0 : redo & 1) ^ (p / 3 & 1));
          if (p >= 2) wg_wait<1>();
#pragma unroll
          for (int s = 0; s < 5; s++) a[s] = lds128(ra + (p % 3) * 2560 + s * 512);
          bad = or3(bad, tag2(a[0].x, a[1].x, ep), tag2(a[2].x, a[3].x, ep)) | tag2(a[4].x, a[4].z, ep);
          if (p < 5) fill(p + 3, bad & blockIdx.y);
          __syncwarp();
          wg_fence();
#pragma unroll
          for (int s = 0; s < 5; s++)
            WG<80>::rs<1>(acc, a[s].x, a[s].y, a[s].z, a[s].w, bd + p * 160 + (s == 4 ? 64 + (64ull << 32) : (s >> 1) * 80 + (s & 1) * 32), (p | s) != 0);
          wg_commit();
        }
        const bool again = __any_sync(0xffffffffu, bar_or(5 + wg, 128, bad & 1u));
        mbar_wait(bars + B_BT, 0);
        if (tid == 0) TS(11);
#pragma unroll
        for (int jj = 0; jj < 5; jj++) ldsm4t(bt + 4 * jj, ba + jj * 4096);
        wg_wait<0>();
        fence_regs<40>(acc);
        if (!again) break;
      }
    }
    if (tid == 0) TS(10);
    {
      uint32_t o[20];
#pragma unroll
      for (int i = 0; i < 20; i++) o[i] = pack(acc[2 * i], acc[2 * i + 1]);
#pragma unroll
      for (int jj = 0; jj < 5; jj++) {
        const uint32_t* b = bt + 4 * jj;
        stsm4(oa + jj * 32, hfma2(b[0], hh[0], o[4 * jj]), hfma2(b[1], hh[1], o[4 * jj + 1]), hfma2(b[2], hh[0], o[4 * jj + 2]), hfma2(b[3], hh[1], o[4 * jj + 3]));
      }
      fence_async_smem();
      __syncwarp();
      if (lane < 16) {
        asm volatile("cp.async.bulk.global.shared::cta.bulk_group [%0], [%1], 160;" ::"l"(og), "r"(orr) : "memory");
        asm volatile("cp.async.bulk.commit_group;" ::: "memory");
        asm volatile("cp.async.bulk.wait_group 0;" ::: "memory");
      }
      if (tid == 0) TS(12);
    }
  }
}

typedef CUresult (*EncFn)(CUtensorMap*, CUtensorMapDataType, cuuint32_t, void*, const cuuint64_t*, const cuuint64_t*, const cuuint32_t*, const cuuint32_t*,
                          CUtensorMapInterleave, CUtensorMapSwizzle, CUtensorMapL2promotion, CUtensorMapFloatOOBfill);
}

extern "C" void kernel_launch(void* const* d_in, const int* in_sizes, int n_in, void* d_out, int out_size) {
  static EncFn enc = nullptr;
  static void* scratch = nullptr;
  if (!enc) {
    cudaDriverEntryPointQueryResult qr;
    cudaGetDriverEntryPoint("cuTensorMapEncodeTiled", (void**)&enc, cudaEnableDefault, &qr);
    cudaFuncSetAttribute(fused_kernel, cudaFuncAttributeMaxDynamicSharedMemorySize, SMEM_BYTES);
    cudaGetSymbolAddress(&scratch, g_s);
  }
  CUtensorMap mx, mw, mwo;
  const cuuint32_t es[5] = {1, 1, 1, 1, 1};
  {
    const cuuint64_t d[2] = {640, 2048}, s[1] = {1280};
    const cuuint32_t b[2] = {64, 256};
    enc(&mx, CU_TENSOR_MAP_DATA_TYPE_BFLOAT16, 2, d_in[0], d, s, b, es, CU_TENSOR_MAP_INTERLEAVE_NONE, CU_TENSOR_MAP_SWIZZLE_128B, CU_TENSOR_MAP_L2_PROMOTION_NONE, CU_TENSOR_MAP_FLOAT_OOB_FILL_NONE);
  }
  {
    const cuuint64_t d[3] = {640, 640, 3}, s[2] = {3840, 1280};
    const cuuint32_t b[3] = {48, 64, 3};
    enc(&mw, CU_TENSOR_MAP_DATA_TYPE_BFLOAT16, 3, d_in[1], d, s, b, es, CU_TENSOR_MAP_INTERLEAVE_NONE, CU_TENSOR_MAP_SWIZZLE_128B, CU_TENSOR_MAP_L2_PROMOTION_NONE, CU_TENSOR_MAP_FLOAT_OOB_FILL_NONE);
  }
  {
    const cuuint64_t d[5] = {640, 2, 4, 5, 16}, s[4] = {1280, 12800, 2560, 51200};
    const cuuint32_t b[5] = {16, 2, 4, 5, 16};
    enc(&mwo, CU_TENSOR_MAP_DATA_TYPE_BFLOAT16, 5, d_in[3], d, s, b, es, CU_TENSOR_MAP_INTERLEAVE_NONE, CU_TENSOR_MAP_SWIZZLE_32B, CU_TENSOR_MAP_L2_PROMOTION_L2_128B, CU_TENSOR_MAP_FLOAT_OOB_FILL_NONE);
  }
  Params P;
  P.wphi = (const __nv_bfloat16*)d_in[2];
  for (int i = 0; i < 4; i++) P.prm[i] = (const __nv_bfloat16*)d_in[5 + i];
  P.logdt = (const __nv_bfloat16*)d_in[9]; P.Dsk = (const __nv_bfloat16*)d_in[10]; P.gw = (const __nv_bfloat16*)d_in[11];
  P.out = (__nv_bfloat16*)d_out;
  P.S = (uint4*)(((uintptr_t)scratch + 4095) & ~(uintptr_t)4095);
  fused_kernel<<<128, 512, SMEM_BYTES>>>(mx, mw, mwo, P);
}
```
